```python
import torch

def _softmax(x, axis=-1):
    return torch.softmax(x, dim=axis)
def _gelu(x):
    return torch.nn.functional.gelu(x, approximate="tanh")
def _silu(x):
    return torch.nn.functional.silu(x)
def _sigmoid(x):
    return torch.sigmoid(x)
def _layernorm(x, axis=-1, eps=1e-5):
    m = x.mean(dim=axis, keepdim=True)
    v = x.var(dim=axis, keepdim=True, unbiased=False)
    return (x - m) / torch.sqrt(v + eps)
def _scatter_add(tgt, idx, src, axis=0):
    return tgt.clone().index_add_(axis, idx, src)
def _segment_sum(src, seg, n):
    out = torch.zeros((n,) + src.shape[1:], dtype=src.dtype)
    return out.index_add_(0, seg, src)
def _pad(x, pw):
    flat = tuple(v for pair in reversed(pw) for v in pair)
    return torch.nn.functional.pad(x, flat)

kernel_name = 'sequential_preLN__spectral_gfnet__glu_gated_swiglu__prompt'

def setup_inputs():

    _w = (lambda a: (lambda t: t.to(torch.bfloat16) if t.is_floating_point() else t)(torch.as_tensor(a)))
    def _A_setup():
        B, S, D = 1, 2048, 640
        Df = D // 2 + 1
        return {
            "x": _w((lambda *s: torch.randn(*s, dtype=torch.bfloat16) * 0.05)(B, S, D)),
            "w_r": _w((lambda *s: torch.randn(*s, dtype=torch.bfloat16) * 0.4)(S, Df) * 0.02),
            "w_i": _w((lambda *s: torch.randn(*s, dtype=torch.bfloat16) * 0.4)(S, Df) * 0.02),
        }
    _A_in = _A_setup()

    def _B_setup():
        B, S, D, F = 1, 2048, 640, 1536
        return {
            "x": _w((lambda *s: torch.randn(*s, dtype=torch.bfloat16) * 0.05)(B, S, D)),
            "w1": _w((lambda *s: torch.randn(*s, dtype=torch.bfloat16) * 0.2)(D, F) * (2.0 / D) ** 0.5),
            "w3": _w((lambda *s: torch.randn(*s, dtype=torch.bfloat16) * 0.2)(D, F) * (2.0 / D) ** 0.5),
            "w2": _w((lambda *s: torch.randn(*s, dtype=torch.bfloat16) * 0.2)(F, D) * (2.0 / F) ** 0.5),
        }
    _B_in = _B_setup()

    return {
        "A_x": _A_in["x"],
        "A_w_r": _A_in["w_r"],
        "A_w_i": _A_in["w_i"],
        "B_x": _B_in["x"],
        "B_w1": _B_in["w1"],
        "B_w3": _B_in["w3"],
        "B_w2": _B_in["w2"],
    }

def reference(A_x, A_w_r, A_w_i, B_x, B_w1, B_w3, B_w2):
    def _A_ref(x, w_r, w_i):
        B, S, D = x.shape
        X = (lambda x, axes=(-2,-1): torch.fft.rfft2(x.float(), dim=axes))(x, axes=(-2, -1))
        W = w_r + 1j * w_i
        X = X * W
        y = (lambda x, s, axes=(-2,-1): torch.fft.irfft2(x, s=s, dim=axes).to(torch.bfloat16))(X, (S, D), axes=(-2, -1))
        return y

    def _B_ref(x, w1, w3, w2):
        gate = torch.einsum("bsd,df->bsf", x, w1)
        up = torch.einsum("bsd,df->bsf", x, w3)
        h = _silu(gate) * up
        out = torch.einsum("bsf,fd->bsd", h, w2)
        return out

    x = A_x
    h = x + _A_ref(_layernorm(x, axis=-1), A_w_r, A_w_i)
    h2 = h + _B_ref(_layernorm(h, axis=-1), B_w1, B_w3, B_w2)
    return h2
```

```cpp
#include <cuda_runtime.h>
#include <cuda_bf16.h>
#include <cuda.h>
#include <stdint.h>
#include <string.h>

#define NCTA 128
#define NTHREADS 512

__device__ __align__(1024) const uint32_t c_T1[2560] = {
0x3f803f80,0xbf803f80,0x3f803f80,0xbf803f80,0x3f803f80,0xbf803f80,0x3f803f80,0xbf803f80,0x3f803f80,0xbf803f80,0x3f803f80,0xbf803f80,
0x3f803f80,0xbf803f80,0x3f803f80,0xbf803f80,0x3f7b3f80,0xbe488000,0xbe480000,0xbf7bbf80,0x3f553f6d,0xbf0ebec4,0xbf0ebec4,0xbf55bf6d,
0x3f0e3f35,0xbf55bf35,0xbf55bf35,0xbf0ebf35,0x3e483ec4,0xbf7bbf6d,0xbf7bbf6d,0xbe48bec4,0x3f6d3f80,0xbec48000,0xbf6dbf80,0x3ec48000,
0x3ec43f35,0xbf6dbf35,0xbec4bf35,0x3f6d3f35,0xbec40000,0xbf6dbf80,0x3ec40000,0x3f6d3f80,0xbf6dbf35,0xbec4bf35,0x3f6d3f35,0x3ec43f35,
0x3f553f80,0xbf0e8000,0x3f0e0000,0x3f553f80,0xbe483ec4,0xbf7bbf6d,0x3f7b3f6d,0xbe483ec4,0xbf7bbf35,0xbe48bf35,0x3e483f35,0xbf7bbf35,
0xbf0ebf6d,0x3f553ec4,0xbf55bec4,0xbf0ebf6d,0x3f353f80,0xbf358000,0x3f353f80,0xbf358000,0xbf350000,0xbf35bf80,0xbf350000,0xbf35bf80,
0xbf35bf80,0x3f358000,0xbf35bf80,0x3f358000,0x3f350000,0x3f353f80,0x3f350000,0x3f353f80,0x3f0e3f80,0xbf558000,0xbf550000,0xbf0ebf80,
0xbf7bbec4,0xbe48bf6d,0xbe48bf6d,0x3f7b3ec4,0x3e48bf35,0x3f7b3f35,0x3f7b3f35,0xbe483f35,0x3f553f6d,0xbf0e3ec4,0xbf0e3ec4,0xbf55bf6d,
0x3ec43f80,0xbf6d8000,0xbec4bf80,0x3f6d8000,0xbf6dbf35,0x3ec4bf35,0x3f6d3f35,0xbec43f35,0x3f6d0000,0x3ec43f80,0xbf6d0000,0xbec4bf80,
0xbec43f35,0xbf6dbf35,0x3ec4bf35,0x3f6d3f35,0x3e483f80,0xbf7b8000,0x3f7b0000,0x3e483f80,0xbf0ebf6d,0x3f55bec4,0xbf553ec4,0xbf0ebf6d,
0x3f553f35,0xbf0e3f35,0x3f0ebf35,0x3f553f35,0xbf7bbec4,0x3e48bf6d,0xbe483f6d,0xbf7bbec4,0x3f803f80,0xbf803f80,0x3f803f80,0xbf803f80,
0x3f803f80,0xbf803f80,0x3f803f80,0xbf803f80,0x3f803f80,0xbf803f80,0x3f803f80,0xbf803f80,0x3f803f80,0xbf803f80,0x3f803f80,0xbf803f80,
0xbf7bbf80,0x3e488000,0x3e480000,0x3f7b3f80,0xbf55bf6d,0x3f0e3ec4,0x3f0e3ec4,0x3f553f6d,0xbf0ebf35,0x3f553f35,0x3f553f35,0x3f0e3f35,
0xbe48bec4,0x3f7b3f6d,0x3f7b3f6d,0x3e483ec4,0x3f6d3f80,0xbec48000,0xbf6dbf80,0x3ec48000,0x3ec43f35,0xbf6dbf35,0xbec4bf35,0x3f6d3f35,
0xbec40000,0xbf6dbf80,0x3ec40000,0x3f6d3f80,0xbf6dbf35,0xbec4bf35,0x3f6d3f35,0x3ec43f35,0xbf55bf80,0x3f0e8000,0xbf0e0000,0xbf55bf80,
0x3e48bec4,0x3f7b3f6d,0xbf7bbf6d,0x3e48bec4,0x3f7b3f35,0x3e483f35,0xbe48bf35,0x3f7b3f35,0x3f0e3f6d,0xbf55bec4,0x3f553ec4,0x3f0e3f6d,
0x3f353f80,0xbf358000,0x3f353f80,0xbf358000,0xbf350000,0xbf35bf80,0xbf350000,0xbf35bf80,0xbf35bf80,0x3f358000,0xbf35bf80,0x3f358000,
0x3f350000,0x3f353f80,0x3f350000,0x3f353f80,0xbf0ebf80,0x3f558000,0x3f550000,0x3f0e3f80,0x3f7b3ec4,0x3e483f6d,0x3e483f6d,0xbf7bbec4,
0xbe483f35,0xbf7bbf35,0xbf7bbf35,0x3e48bf35,0xbf55bf6d,0x3f0ebec4,0x3f0ebec4,0x3f553f6d,0x3ec43f80,0xbf6d8000,0xbec4bf80,0x3f6d8000,
0xbf6dbf35,0x3ec4bf35,0x3f6d3f35,0xbec43f35,0x3f6d0000,0x3ec43f80,0xbf6d0000,0xbec4bf80,0xbec43f35,0xbf6dbf35,0x3ec4bf35,0x3f6d3f35,
0xbe48bf80,0x3f7b8000,0xbf7b0000,0xbe48bf80,0x3f0e3f6d,0xbf553ec4,0x3f55bec4,0x3f0e3f6d,0xbf55bf35,0x3f0ebf35,0xbf0e3f35,0xbf55bf35,
0x3f7b3ec4,0xbe483f6d,0x3e48bf6d,0x3f7b3ec4,0x3f80,0xbf808000,0x3f80,0xbf808000,0xbf80,0x3f808000,0xbf80,0x3f808000,
0x3f80,0xbf808000,0x3f80,0xbf808000,0xbf80,0x3f808000,0xbf80,0x3f808000,0xbe483f80,0xbf7b8000,0xbf7b0000,0x3e48bf80,
0x3f0ebf6d,0x3f553ec4,0x3f553ec4,0xbf0e3f6d,0xbf553f35,0xbf0ebf35,0xbf0ebf35,0x3f55bf35,0x3f7bbec4,0x3e483f6d,0x3e483f6d,0xbf7b3ec4,
0xbec43f80,0xbf6d8000,0x3ec4bf80,0x3f6d8000,0x3f6dbf35,0x3ec43f35,0xbf6d3f35,0xbec4bf35,0xbf6d0000,0x3ec4bf80,0x3f6d0000,0xbec43f80,
0x3ec43f35,0xbf6d3f35,0xbec4bf35,0x3f6dbf35,0xbf0e3f80,0xbf558000,0x3f550000,0xbf0e3f80,0x3f7bbec4,0xbe483f6d,0x3e48bf6d,0x3f7bbec4,
0xbe48bf35,0x3f7bbf35,0xbf7b3f35,0xbe48bf35,0xbf553f6d,0xbf0ebec4,0x3f0e3ec4,0xbf553f6d,0xbf353f80,0xbf358000,0xbf353f80,0xbf358000,
0x3f350000,0xbf353f80,0x3f350000,0xbf353f80,0x3f35bf80,0x3f358000,0x3f35bf80,0x3f358000,0xbf350000,0x3f35bf80,0xbf350000,0x3f35bf80,
0xbf553f80,0xbf0e8000,0xbf0e0000,0x3f55bf80,0x3e483ec4,0xbf7b3f6d,0xbf7b3f6d,0xbe48bec4,0x3f7bbf35,0xbe483f35,0xbe483f35,0xbf7b3f35,
0x3f0ebf6d,0x3f55bec4,0x3f55bec4,0xbf0e3f6d,0xbf6d3f80,0xbec48000,0x3f6dbf80,0x3ec48000,0xbec43f35,0xbf6d3f35,0x3ec4bf35,0x3f6dbf35,
0x3ec40000,0xbf6d3f80,0xbec40000,0x3f6dbf80,0x3f6dbf35,0xbec43f35,0xbf6d3f35,0x3ec4bf35,0xbf7b3f80,0xbe488000,0x3e480000,0xbf7b3f80,
0xbf553f6d,0xbf0e3ec4,0x3f0ebec4,0xbf553f6d,0xbf0e3f35,0xbf553f35,0x3f55bf35,0xbf0e3f35,0xbe483ec4,0xbf7b3f6d,0x3f7bbf6d,0xbe483ec4,
0x3f80,0xbf808000,0x3f80,0xbf808000,0xbf80,0x3f808000,0xbf80,0x3f808000,0x3f80,0xbf808000,0x3f80,0xbf808000,
0xbf80,0x3f808000,0xbf80,0x3f808000,0x3e48bf80,0x3f7b8000,0x3f7b0000,0xbe483f80,0xbf0e3f6d,0xbf55bec4,0xbf55bec4,0x3f0ebf6d,
0x3f55bf35,0x3f0e3f35,0x3f0e3f35,0xbf553f35,0xbf7b3ec4,0xbe48bf6d,0xbe48bf6d,0x3f7bbec4,0xbec43f80,0xbf6d8000,0x3ec4bf80,0x3f6d8000,
0x3f6dbf35,0x3ec43f35,0xbf6d3f35,0xbec4bf35,0xbf6d0000,0x3ec4bf80,0x3f6d0000,0xbec43f80,0x3ec43f35,0xbf6d3f35,0xbec4bf35,0x3f6dbf35,
0x3f0ebf80,0x3f558000,0xbf550000,0x3f0ebf80,0xbf7b3ec4,0x3e48bf6d,0xbe483f6d,0xbf7b3ec4,0x3e483f35,0xbf7b3f35,0x3f7bbf35,0x3e483f35,
0x3f55bf6d,0x3f0e3ec4,0xbf0ebec4,0x3f55bf6d,0xbf353f80,0xbf358000,0xbf353f80,0xbf358000,0x3f350000,0xbf353f80,0x3f350000,0xbf353f80,
0x3f35bf80,0x3f358000,0x3f35bf80,0x3f358000,0xbf350000,0x3f35bf80,0xbf350000,0x3f35bf80,0x3f55bf80,0x3f0e8000,0x3f0e0000,0xbf553f80,
0xbe48bec4,0x3f7bbf6d,0x3f7bbf6d,0x3e483ec4,0xbf7b3f35,0x3e48bf35,0x3e48bf35,0x3f7bbf35,0xbf0e3f6d,0xbf553ec4,0xbf553ec4,0x3f0ebf6d,
0xbf6d3f80,0xbec48000,0x3f6dbf80,0x3ec48000,0xbec43f35,0xbf6d3f35,0x3ec4bf35,0x3f6dbf35,0x3ec40000,0xbf6d3f80,0xbec40000,0x3f6dbf80,
0x3f6dbf35,0xbec43f35,0xbf6d3f35,0x3ec4bf35,0x3f7bbf80,0x3e488000,0xbe480000,0x3f7bbf80,0x3f55bf6d,0x3f0ebec4,0xbf0e3ec4,0x3f55bf6d,
0x3f0ebf35,0x3f55bf35,0xbf553f35,0x3f0ebf35,0x3e48bec4,0x3f7bbf6d,0xbf7b3f6d,0x3e48bec4,0x3f800000,0x0,0x3f800000,0x0,
0x3f800000,0x0,0x3f800000,0x0,0x3f800000,0x0,0x3f800000,0x0,0x3f800000,0x0,0x3f800000,0x0,
0x3f800000,0x0,0x3f7ffcd7,0x3c20d8d2,0x3f7ff35e,0x3ca0d6d6,0x3f7fe394,0x3cf13d4c,0x3f7fcd79,0x3d20cee7,0x3f7fb10f,0x3d48fb30,
0x3f7f8e56,0x3d712283,0x3f7f654e,0x3d8ca1f2,0x3f800000,0x0,0x3f7ff35e,0x3ca0d6d6,0x3f7fcd79,0x3d20cee7,0x3f7f8e56,0x3d712283,
0x3f7f35f9,0x3da0af2a,0x3f7ec46d,0x3dc8bd36,0x3f7e39bc,0x3df0b772,0x3f7d95f4,0x3e0c4cf7,0x3f800000,0x0,0x3f7fe394,0x3cf13d4c,
0x3f7f8e56,0x3d712283,0x3f7f0059,0x3db4b86a,0x3f7e39bc,0x3df0b772,0x3f7d3aac,0x3e164083,0x3f7c0361,0x3e3403f1,0x3f7a9421,0x3e519f65,
0x3f800000,0x0,0x3f7fcd79,0x3d20cee7,0x3f7f35f9,0x3da0af2a,0x3f7e39bc,0x3df0b772,0x3f7cd925,0x3e20305b,0x3f7b14be,0x3e47c5c2,
0x3f78ed3c,0x3e6f0c4d,0x3f766377,0x3e8afa3e,0x3f800000,0x0,0x3f7fb10f,0x3d48fb30,0x3f7ec46d,0x3dc8bd36,0x3f7d3aac,0x3e164083,
0x3f7b14be,0x3e47c5c2,0x3f7853f8,0x3e78cfcc,0x3f74fa0b,0x3e94a031,0x3f710908,0x3eac7cd4,0x3f800000,0x0,0x3f7f8e56,0x3d712283,
0x3f7e39bc,0x3df0b772,0x3f7c0361,0x3e3403f1,0x3f78ed3c,0x3e6f0c4d,0x3f74fa0b,0x3e94a031,0x3f702d4f,0x3eb13641,0x3f6a8b4b,0x3ecd2ef3,
0x3f800000,0x0,0x3f7f654e,0x3d8ca1f2,0x3f7d95f4,0x3e0c4cf7,0x3f7a9421,0x3e519f65,0x3f766377,0x3e8afa3e,0x3f710908,0x3eac7cd4,
0x3f6a8b4b,0x3ecd2ef3,0x3f62f219,0x3eece91a,0x3f800000,0x0,0x3f800000,0x0,0x3f800000,0x0,0x3f800000,0x0,
0x3f800000,0x0,0x3f800000,0x0,0x3f800000,0x0,0x3f800000,0x0,0x3f7f35f9,0x3da0af2a,0x3f7f0059,0x3db4b86a,
0x3f7ec46d,0x3dc8bd36,0x3f7e8238,0x3ddcbd0d,0x3f7e39bc,0x3df0b772,0x3f7deafa,0x3e0255f4,0x3f7d95f4,0x3e0c4cf7,0x3f7d3aac,0x3e164083,
0x3f7cd925,0x3e20305b,0x3f7c0361,0x3e3403f1,0x3f7b14be,0x3e47c5c2,0x3f7a0d54,0x3e5b73dc,0x3f78ed3c,0x3e6f0c4d,0x3f77b493,0x3e814693,
0x3f766377,0x3e8afa3e,0x3f74fa0b,0x3e94a031,0x3f78ed3c,0x3e6f0c4d,0x3f770f11,0x3e862210,0x3f74fa0b,0x3e94a031,0x3f72ae9e,0x3ea2fd52,
0x3f702d4f,0x3eb13641,0x3f6d76aa,0x3ebf47d7,0x3f6a8b4b,0x3ecd2ef3,0x3f676bd8,0x3edae880,0x3f737871,0x3e9e377a,0x3f702d4f,0x3eb13641,
0x3f6c835e,0x3ec3ef15,0x3f687c12,0x3ed65a92,0x3f641901,0x3ee87171,0x3f5f5be6,0x3efa2c90,0x3f5a46a0,0x3f05c277,0x3f54db31,0x3f0e39da,
0x3f6c835e,0x3ec3ef15,0x3f676bd8,0x3edae880,0x3f61c598,0x3ef15aea,0x3f5b941a,0x3f039c3d,0x3f54db31,0x3f0e39da,0x3f4d9f02,0x3f187fc0,
0x3f45e403,0x3f226799,0x3f3daef9,0x3f2beb4a,0x3f641901,0x3ee87171,0x3f5cdc29,0x3f0172c3,0x3f54db31,0x3f0e39da,0x3f4c1d35,0x3f1a82a4,
0x3f42a9f7,0x3f26423a,0x3f3889dc,0x3f316e2c,0x3f2dc5e3,0x3f3bfc8f,0x3f226799,0x3f45e403,0x3f5a46a0,0x3f05c277,0x3f50935b,0x3f146eba,
0x3f45e403,0x3f226799,0x3f3a4582,0x3f2f9c32,0x3f2dc5e3,0x3f3bfc8f,0x3f207440,0x3f4779bc,0x3f1260b2,0x3f5205d4,0x3f039c3d,0x3f5b941a,
0x3f800000,0x0,0x3f800000,0x0,0x3f800000,0x0,0x3f800000,0x0,0x0,0x0,0x0,0x0,
0x0,0x0,0x0,0x0,0x3f7cd925,0x3e20305b,0x3f7c7160,0x3e2a1c3f,0x3f7c0361,0x3e3403f1,0x3f7b8f2a,0x3e3de731,
0x0,0x0,0x0,0x0,0x0,0x0,0x0,0x0,0x3f737871,0x3e9e377a,0x3f71decf,0x3ea7bf25,
0x3f702d4f,0x3eb13641,0x3f6e641a,0x3eba9be1,0x0,0x0,0x0,0x0,0x0,0x0,0x0,0x0,
0x3f641901,0x3ee87171,0x3f609384,0x3ef5c6c5,0x3f5cdc29,0x3f0172c3,0x3f58f3c4,0x3f07e565,0x0,0x0,0x0,0x0,
0x0,0x0,0x0,0x0,0x3f4f1bbd,0x3f167918,0x3f490a88,0x3f1e7cf1,0x3f42a9f7,0x3f26423a,0x3f3bfc8f,0x3f2dc5e3,
0x0,0x0,0x0,0x0,0x0,0x0,0x0,0x0,0x3f3504f3,0x3f3504f3,0x3f2beb4a,0x3f3daef9,
0x3f226799,0x3f45e403,0x3f187fc0,0x3f4d9f02,0x0,0x0,0x0,0x0,0x0,0x0,0x0,0x0,
0x3f167918,0x3f4f1bbd,0x3f0a04f8,0x3f579b8c,0x3efa2c90,0x3f5f5be6,0x3edf7108,0x3f6655e7,0x0,0x0,0x0,0x0,
0x0,0x0,0x0,0x0,0x3ee87171,0x3f641901,0x3ec8917e,0x3f6b8a3d,0x3ea7bf25,0x3f71decf,0x3e862210,0x3f770f11,
0x0,0x0,0x0,0x0,0x0,0x0,0x0,0x0,0x3f800000,0x0,0x3f7f35f9,0x3da0af2a,
0x3f7cd925,0x3e20305b,0x3f78ed3c,0x3e6f0c4d,0x3f737871,0x3e9e377a,0x3f6c835e,0x3ec3ef15,0x3f641901,0x3ee87171,0x3f5a46a0,0x3f05c277,
0x3f800000,0x0,0x3f7f0059,0x3db4b86a,0x3f7c0361,0x3e3403f1,0x3f770f11,0x3e862210,0x3f702d4f,0x3eb13641,0x3f676bd8,0x3edae880,
0x3f5cdc29,0x3f0172c3,0x3f50935b,0x3f146eba,0x3f800000,0x0,0x3f7ec46d,0x3dc8bd36,0x3f7b14be,0x3e47c5c2,0x3f74fa0b,0x3e94a031,
0x3f6c835e,0x3ec3ef15,0x3f61c598,0x3ef15aea,0x3f54db31,0x3f0e39da,0x3f45e403,0x3f226799,0x3f800000,0x0,0x3f7e8238,0x3ddcbd0d,
0x3f7a0d54,0x3e5b73dc,0x3f72ae9e,0x3ea2fd52,0x3f687c12,0x3ed65a92,0x3f5b941a,0x3f039c3d,0x3f4c1d35,0x3f1a82a4,0x3f3a4582,0x3f2f9c32,
0x3f800000,0x0,0x3f7e39bc,0x3df0b772,0x3f78ed3c,0x3e6f0c4d,0x3f702d4f,0x3eb13641,0x3f641901,0x3ee87171,0x3f54db31,0x3f0e39da,
0x3f42a9f7,0x3f26423a,0x3f2dc5e3,0x3f3bfc8f,0x3f800000,0x0,0x3f7deafa,0x3e0255f4,0x3f77b493,0x3e814693,0x3f6d76aa,0x3ebf47d7,
0x3f5f5be6,0x3efa2c90,0x3f4d9f02,0x3f187fc0,0x3f3889dc,0x3f316e2c,0x3f207440,0x3f4779bc,0x3f800000,0x0,0x3f7d95f4,0x3e0c4cf7,
0x3f766377,0x3e8afa3e,0x3f6a8b4b,0x3ecd2ef3,0x3f5a46a0,0x3f05c277,0x3f45e403,0x3f226799,0x3f2dc5e3,0x3f3bfc8f,0x3f1260b2,0x3f5205d4,
0x3f800000,0x0,0x3f7d3aac,0x3e164083,0x3f74fa0b,0x3e94a031,0x3f676bd8,0x3edae880,0x3f54db31,0x3f0e39da,0x3f3daef9,0x3f2beb4a,
0x3f226799,0x3f45e403,0x3f039c3d,0x3f5b941a,0x3f4f1bbd,0x3f167918,0x3f42a9f7,0x3f26423a,0x3f3504f3,0x3f3504f3,0x3f26423a,0x3f42a9f7,
0x3f167918,0x3f4f1bbd,0x3f05c277,0x3f5a46a0,0x3ee87171,0x3f641901,0x3ec3ef15,0x3f6c835e,0x3f42a9f7,0x3f26423a,0x3f333bc6,0x3f36c9a9,
0x3f226799,0x3f45e403,0x3f104f0e,0x3f53731f,0x3efa2c90,0x3f5f5be6,0x3ed1c759,0x3f698690,0x3ea7bf25,0x3f71decf,0x3e78cfcc,0x3f7853f8,
0x3f3504f3,0x3f3504f3,0x3f226799,0x3f45e403,0x3f0e39da,0x3f54db31,0x3ef15aea,0x3f61c598,0x3ec3ef15,0x3f6c835e,0x3e94a031,0x3f74fa0b,
0x3e47c5c2,0x3f7b14be,0x3dc8bd36,0x3f7ec46d,0x3f26423a,0x3f42a9f7,0x3f104f0e,0x3f53731f,0x3ef15aea,0x3f61c598,0x3ebf47d7,0x3f6d76aa,
0x3e8afa3e,0x3f766377,0x3e2a1c3f,0x3f7c7160,0x3d712283,0x3f7f8e56,0xbd48fb30,0x3f7fb10f,0x3f167918,0x3f4f1bbd,0x3efa2c90,0x3f5f5be6,
0x3ec3ef15,0x3f6c835e,0x3e8afa3e,0x3f766377,0x3e20305b,0x3f7cd925,0x3d20cee7,0x3f7fcd79,0xbda0af2a,0x3f7f35f9,0xbe47c5c2,0x3f7b14be,
0x3f05c277,0x3f5a46a0,0x3ed1c759,0x3f698690,0x3e94a031,0x3f74fa0b,0x3e2a1c3f,0x3f7c7160,0x3d20cee7,0x3f7fcd79,0xbdb4b86a,0x3f7f0059,
0xbe5b73dc,0x3f7a0d54,0xbeac7cd4,0x3f710908,0x3ee87171,0x3f641901,0x3ea7bf25,0x3f71decf,0x3e47c5c2,0x3f7b14be,0x3d712283,0x3f7f8e56,
0xbda0af2a,0x3f7f35f9,0xbe5b73dc,0x3f7a0d54,0xbeb13641,0x3f702d4f,0xbef15aea,0x3f61c598,0x3ec3ef15,0x3f6c835e,0x3e78cfcc,0x3f7853f8,
0x3dc8bd36,0x3f7ec46d,0xbd48fb30,0x3f7fb10f,0xbe47c5c2,0x3f7b14be,0xbeac7cd4,0x3f710908,0xbef15aea,0x3f61c598,0xbf187fc0,0x3f4d9f02,
0x3e9e377a,0x3f737871,0x3e6f0c4d,0x3f78ed3c,0x3e20305b,0x3f7cd925,0x3da0af2a,0x3f7f35f9,0x0,0x0,0x0,0x0,
0x0,0x0,0x0,0x0,0x3e20305b,0x3f7cd925,0x3d8ca1f2,0x3f7f654e,0xbca0d6d6,0x3f7ff35e,0xbddcbd0d,0x3f7e8238,
0x0,0x0,0x0,0x0,0x0,0x0,0x0,0x0,0x0,0x3f800000,0xbdc8bd36,0x3f7ec46d,
0xbe47c5c2,0x3f7b14be,0xbe94a031,0x3f74fa0b,0x0,0x0,0x0,0x0,0x0,0x0,0x0,0x0,
0xbe20305b,0x3f7cd925,0xbe862210,0x3f770f11,0xbeba9be1,0x3f6e641a,0xbeece91a,0x3f62f219,0x0,0x0,0x0,0x0,
0x0,0x0,0x0,0x0,0xbe9e377a,0x3f737871,0xbed65a92,0x3f687c12,0xbf05c277,0x3f5a46a0,0xbf1e7cf1,0x3f490a88,
0x0,0x0,0x0,0x0,0x0,0x0,0x0,0x0,0xbee87171,0x3f641901,0xbf104f0e,0x3f53731f,
0xbf2a0c73,0x3f3f5cb5,0xbf4105b8,0x3f28296a,0x0,0x0,0x0,0x0,0x0,0x0,0x0,0x0,
0xbf167918,0x3f4f1bbd,0xbf316e2c,0x3f3889dc,0xbf490a88,0x3f1e7cf1,0xbf5cdc29,0x3f0172c3,0x0,0x0,0x0,0x0,
0x0,0x0,0x0,0x0,0xbf3504f3,0x3f3504f3,0xbf4d9f02,0x3f187fc0,0xbf61c598,0x3ef15aea,0xbf710908,0x3eac7cd4,
0x0,0x0,0x0,0x0,0x0,0x0,0x0,0x0,0x3f803f80,0x0,0x3e9e3f80,0x3f730000,
0x3f803f80,0x0,0xbf4fbf4f,0xbf163f16,0x3f803f80,0x0,0x3f803e9e,0xbf73,0x3f803f80,0x0,0xbf4f3e9e,0x3f163f73,
0x80008000,0x3f803f80,0xbf738000,0x3e9e3f80,0x80008000,0x3f803f80,0x3f16bf16,0xbf4fbf4f,0x80008000,0x3f803f80,0x80003f73,0x3f803e9e,
0x80008000,0x3f803f80,0xbf16bf73,0xbf4f3e9e,0x3f733f80,0x3e9e0000,0x3f80,0x3f800000,0x3f163f4f,0x3f4f3f16,0xbf80,0xbf800000,
0x3e9e,0x3f803f73,0x3f80,0x3f800000,0xbf16be9e,0x3f4f3f73,0xbf80,0xbf800000,0xbe9e8000,0x3f733f80,0xbf808000,0x3f80,
0xbf4fbf16,0x3f163f4f,0x3f808000,0xbf80,0xbf80bf73,0x3e9e,0xbf808000,0x3f80,0xbf4fbf73,0xbf16be9e,0x3f808000,0xbf80,
0x3f4f3f80,0x3f160000,0xbe9e3f80,0x3f730000,0xbe9e3e9e,0x3f733f73,0x3f4fbf4f,0xbf16bf16,0xbf80bf4f,0x3f16,0xbf803e9e,0x3f73,
0xbe9ebf4f,0xbf73bf16,0x3f4f3e9e,0x3f16bf73,0xbf168000,0x3f4f3f80,0xbf738000,0xbe9e3f80,0xbf73bf73,0xbe9e3e9e,0x3f163f16,0x3f4fbf4f,
0x8000bf16,0xbf80bf4f,0x8000bf73,0xbf803e9e,0x3f733f16,0xbe9ebf4f,0xbf163f73,0x3f4f3e9e,0x3f163f80,0x3f4f0000,0xbf163f80,0x3f4f0000,
0xbf73be9e,0x3e9e3f73,0x3f73be9e,0x3e9ebf73,0xbf4f,0xbf80bf16,0xbf4f,0xbf803f16,0x3f733f4f,0x3e9ebf16,0xbf733f4f,0x3e9e3f16,
0xbf4f8000,0x3f163f80,0xbf4f8000,0xbf163f80,0xbe9ebf73,0xbf73be9e,0xbe9e3f73,0x3f73be9e,0x3f803f16,0xbf4f,0x3f80bf16,0xbf4f,
0xbe9e3f16,0x3f733f4f,0xbe9ebf16,0xbf733f4f,0xbf4f3f80,0x3f160000,0xbf4f3f80,0xbf160000,0x3e9e3e9e,0x3f73bf73,0x3e9e3e9e,0xbf733f73,
0x3f80bf4f,0xbf16,0x3f80bf4f,0x3f16,0x3e9ebf4f,0xbf733f16,0x3e9ebf4f,0x3f73bf16,0xbf168000,0xbf4f3f80,0xbf160000,0x3f4fbf80,
0xbf733f73,0x3e9e3e9e,0xbf733f73,0xbe9ebe9e,0x80003f16,0x3f80bf4f,0x3f16,0xbf803f4f,0x3f73bf16,0x3e9ebf4f,0x3f73bf16,0xbe9e3f4f,
0xbf733f80,0x3e9e0000,0xbf163f80,0xbf4f0000,0xbf163f4f,0x3f4fbf16,0x3f73be9e,0xbe9e3f73,0x3e9e,0x3f80bf73,0xbf4f,0x3f80bf16,
0x3f16be9e,0x3f4fbf73,0xbf733f4f,0xbe9ebf16,0xbe9e8000,0xbf733f80,0xbf4f0000,0x3f16bf80,0xbf4f3f16,0xbf163f4f,0xbe9e3f73,0xbf733e9e,
0xbf803f73,0x3e9e,0x3f80bf16,0x80003f4f,0xbf4f3f73,0x3f16be9e,0xbe9ebf16,0x3f73bf4f,0xbf803f80,0x0,0xbe9e3f80,0xbf730000,
0xbf803f80,0x0,0x3f4fbf4f,0x3f163f16,0xbf803f80,0x0,0xbf803e9e,0xbf73,0xbf803f80,0x0,0x3f4f3e9e,0xbf163f73,
0x0,0x3f80bf80,0xbf730000,0x3e9ebf80,0x0,0x3f80bf80,0x3f163f16,0xbf4f3f4f,0x0,0x3f80bf80,0xbf73,0x3f80be9e,
0x0,0x3f80bf80,0xbf163f73,0xbf4fbe9e,0xbf733f80,0xbe9e0000,0x3f80,0xbf800000,0xbf163f4f,0xbf4f3f16,0xbf80,0x3f800000,
0x3e9e,0xbf803f73,0x3f80,0xbf800000,0x3f16be9e,0xbf4f3f73,0xbf80,0x3f800000,0xbe9e0000,0x3f73bf80,0xbf800000,0x8000bf80,
0xbf4f3f16,0x3f16bf4f,0x3f800000,0x80003f80,0xbf803f73,0x8000be9e,0xbf800000,0x8000bf80,0xbf4f3f73,0xbf163e9e,0x3f800000,0x80003f80,
0x3e9e3f80,0xbf730000,0x3f803f80,0x0,0xbf4fbf4f,0x3f16bf16,0x3f803f80,0x0,0x3f803e9e,0x3f73,0x3f803f80,0x0,
0xbf4f3e9e,0xbf16bf73,0x3f803f80,0x0,0xbf730000,0xbe9ebf80,0x80008000,0x3f803f80,0x3f16bf16,0x3f4f3f4f,0x80008000,0x3f803f80,
0x3f73,0xbf80be9e,0x80008000,0x3f803f80,0xbf16bf73,0x3f4fbe9e,0x80008000,0x3f803f80,0x3f163f80,0xbf4f0000,0xbf73bf4f,0x3e9e3f16,
0xbf73be9e,0xbe9ebf73,0xbf73bf80,0xbe9e0000,0xbf4f,0x3f803f16,0xbf16bf4f,0xbf4fbf16,0x3f733f4f,0xbe9e3f16,0xbe9e,0xbf80bf73,
0xbf4f0000,0xbf16bf80,0xbe9ebf16,0xbf73bf4f,0xbe9ebf73,0x3f733e9e,0x3e9e8000,0xbf73bf80,0x3f803f16,0x80003f4f,0x3f4f3f16,0xbf16bf4f,
0xbe9e3f16,0xbf73bf4f,0x3f803f73,0xbe9e,0x3f4f3f80,0xbf160000,0x3f4f3e9e,0xbf16bf73,0xbe9e3e9e,0xbf73bf73,0x3f4f3f80,0x3f160000,
0xbf80bf4f,0xbf16,0xbe9e3e9e,0x3f733f73,0xbe9ebf4f,0x3f733f16,0xbf80bf4f,0x3f16,0xbf160000,0xbf4fbf80,0x3f163f73,0x3f4f3e9e,
0xbf73bf73,0x3e9ebe9e,0xbf168000,0x3f4f3f80,0xbf16,0x3f803f4f,0xbf73bf73,0xbe9e3e9e,0x3f733f16,0x3e9e3f4f,0x8000bf16,0xbf80bf4f,
0x3f733f80,0xbe9e0000,0xbf163e9e,0x3f4f3f73,0x3f163f4f,0xbf4fbf16,0xbf16bf80,0xbf4f0000,0x3e9e,0xbf80bf73,0x3f733e9e,0xbe9ebf73,
0xbf16be9e,0xbf4fbf73,0x3f4f,0x3f803f16,0xbe9e0000,0xbf73bf80,0xbf4fbf73,0xbf163e9e,0xbf4fbf16,0xbf16bf4f,0x3f4f8000,0xbf16bf80,
0xbf80bf73,0x8000be9e,0x3e9e3f73,0x3f733e9e,0xbf4fbf73,0x3f163e9e,0xbf80bf16,0x3f4f,0x3e9ebf4f,0xbf73bf16,0xbf4f3e9e,0xbf163f73,
0x3e9e3f80,0x3f730000,0xbf4f3f80,0x3f160000,0xbf4fbf4f,0xbf163f16,0x3e9e3e9e,0x3f73bf73,0x3f803e9e,0xbf73,0x3f80bf4f,0xbf16,
0x3f733f16,0x3e9ebf4f,0x3f16bf73,0xbf4f3e9e,0xbf738000,0x3e9e3f80,0xbf168000,0xbf4f3f80,0x3f16bf16,0xbf4fbf4f,0xbf733f73,0x3e9e3e9e,
0x80003f73,0x3f803e9e,0x80003f16,0x3f80bf4f,0x3f80,0x3f800000,0x3f73bf4f,0x3e9ebf16,0xbf80,0xbf800000,0x3f73bf80,0xbe9e0000,
0x3f80,0x3f800000,0x3f16bf4f,0xbf4f3f16,0xbf80,0xbf800000,0xbe9e,0xbf803f73,0xbf808000,0x3f80,0xbe9e3f16,0x3f73bf4f,
0x3f808000,0xbf80,0x3e9e8000,0x3f73bf80,0xbf808000,0x3f80,0x3f4fbf16,0x3f16bf4f,0x3f808000,0xbf80,0x3f80bf73,0xbe9e,
0xbe9ebf4f,0xbf733f16,0xbf803f80,0x0,0xbe9e3f80,0x3f730000,0xbf803f80,0x0,0x3f4fbf4f,0xbf16bf16,0xbf803f80,0x0,
0xbf803e9e,0x3f73,0xbf803f80,0x0,0x3f73bf16,0xbe9ebf4f,0x0,0x3f80bf80,0xbf738000,0xbe9e3f80,0x0,0x3f80bf80,
0x3f163f16,0x3f4fbf4f,0x0,0x3f80bf80,0x8000bf73,0xbf803e9e,0x0,0x3f80bf80,0x3f163e9e,0x3f4fbf73,0x3f73bf4f,0xbe9e3f16,
0x3f16bf80,0xbf4f0000,0x3f73bf80,0x3e9e0000,0xbf733e9e,0xbe9e3f73,0x3f16bf4f,0x3f4fbf16,0x3f4f,0x3f80bf16,0xbe9e,0x3f80bf73,
0xbf4f3f73,0x3f163e9e,0xbe9e3f16,0xbf733f4f,0x3f4f8000,0x3f16bf80,0x3e9e0000,0xbf733f80,0x3e9ebf73,0xbf733e9e,0x3f4fbf16,0xbf163f4f,
0xbf803f16,0x3f4f,0x3f80bf73,0x80003e9e,0xbf4f3e9e,0x3f16bf73,0x3e9ebf4f,0x3f733f16,0xbf4f3f80,0xbf160000,0x3e9e3f80,0xbf730000,
0x3e9e3e9e,0xbf733f73,0xbf4fbf4f,0x3f16bf16,0x3f80bf4f,0x3f16,0x3f803e9e,0x3f73,0x3f16bf73,0x3f4fbe9e,0x3f733f16,0xbe9e3f4f,
0xbf160000,0x3f4fbf80,0xbf730000,0xbe9ebf80,0xbf733f73,0xbe9ebe9e,0x3f16bf16,0x3f4f3f4f,0x3f16,0xbf803f4f,0x3f73,0xbf80be9e,
0x3f163e9e,0xbf4f3f73,0xbf163e9e,0xbf4fbf73,0x3f16bf80,0x3f4f0000,0xbf16bf80,0x3f4f0000,0xbf733e9e,0x3e9ebf73,0x3f733e9e,0x3e9e3f73,
0x3f4f,0xbf803f16,0x3f4f,0xbf80bf16,0xbf4f3f73,0xbf16be9e,0xbf4fbf73,0x3f16be9e,0x3f4f0000,0xbf163f80,0x3f4f0000,0x3f163f80,
0x3e9ebf73,0x3f73be9e,0x3e9e3f73,0xbf73be9e,0xbf803f16,0x8000bf4f,0xbf80bf16,0x8000bf4f,0xbe9ebf4f,0x3f73bf16,0x3f4f3e9e,0x3f163f73,
0xbe9e3f80,0xbf730000,0x3f4f3f80,0xbf160000,0x3f4fbf4f,0x3f163f16,0xbe9e3e9e,0xbf73bf73,0xbf803e9e,0xbf73,0xbf80bf4f,0xbf16,
0x3f73bf16,0x3e9e3f4f,0x3f163f73,0xbf4fbe9e,0xbf730000,0x3e9ebf80,0xbf160000,0xbf4fbf80,0x3f163f16,0xbf4f3f4f,0xbf73bf73,0x3e9ebe9e,
0xbf73,0x3f80be9e,0xbf16,0x3f803f4f,0x3f80,0xbf800000,0xbf73bf4f,0xbe9ebf16,0xbf80,0x3f800000,0xbf73bf80,0x3e9e0000,
0x3f80,0xbf800000,0xbf16bf4f,0x3f4f3f16,0xbf80,0x3f800000,0xbe9e,0x3f803f73,0xbf800000,0x8000bf80,0xbe9ebf16,0x3f733f4f,
0x3f800000,0x80003f80,0x3e9e0000,0x3f733f80,0xbf800000,0x8000bf80,0x3f4f3f16,0x3f163f4f,0x3f800000,0x80003f80,0x3f803f73,0x80003e9e,
0x3f803f80,0x0,0xbf4f3e9e,0x3f163f73,0x3f803f80,0x0,0x3e9ebf4f,0xbf73bf16,0x0,0x0,0x0,0x0,
0x0,0x0,0x0,0x0,0x80008000,0x3f803f80,0xbf16bf73,0xbf4f3e9e,0x80008000,0x3f803f80,0x3f733f16,0x3e9ebf4f,
0x0,0x0,0x0,0x0,0x0,0x0,0x0,0x0,0x3f163e9e,0xbf4fbf73,0x3f80,0x3f800000,
0x3f733f4f,0xbe9ebf16,0xbf80,0xbf800000,0x0,0x0,0x0,0x0,0x0,0x0,0x0,0x0,
0x3f4f3f73,0x3f163e9e,0xbf808000,0x3f80,0x3e9e3f16,0x3f733f4f,0x3f808000,0xbf80,0x0,0x0,0x0,0x0,
0x0,0x0,0x0,0x0,0xbe9ebf4f,0xbf73bf16,0x3f4f3e9e,0x3f16bf73,0x3f4f3e9e,0xbf16bf73,0xbe9ebf4f,0xbf733f16,
0x0,0x0,0x0,0x0,0x0,0x0,0x0,0x0,0x3f733f16,0xbe9ebf4f,0xbf163f73,0x3f4f3e9e,
0x3f163f73,0x3f4f3e9e,0x3f73bf16,0xbe9ebf4f,0x0,0x0,0x0,0x0,0x0,0x0,0x0,0x0,
0xbf73bf4f,0xbe9e3f16,0x3f73bf4f,0xbe9ebf16,0x3f16be9e,0xbf4fbf73,0xbf16be9e,0xbf4f3f73,0x0,0x0,0x0,0x0,
0x0,0x0,0x0,0x0,0x3e9ebf16,0xbf73bf4f,0x3e9e3f16,0x3f73bf4f,0x3f4f3f73,0x3f16be9e,0x3f4fbf73,0xbf16be9e,
0x0,0x0,0x0,0x0,0x0,0x0,0x0,0x0,0x3e9ebf4f,0xbf733f16,0x3e9ebf4f,0x3f73bf16,
0xbf4f3e9e,0xbf163f73,0xbf4f3e9e,0x3f16bf73,0x0,0x0,0x0,0x0,0x0,0x0,0x0,0x0,
0x3f73bf16,0x3e9ebf4f,0x3f73bf16,0xbe9e3f4f,0x3f16bf73,0xbf4f3e9e,0x3f16bf73,0x3f4fbe9e,0x0,0x0,0x0,0x0,
0x0,0x0,0x0,0x0,0xbf163e9e,0xbf4f3f73,0x3f73bf4f,0x3e9e3f16,0xbf733f4f,0xbe9e3f16,0xbf16be9e,0x3f4fbf73,
0x0,0x0,0x0,0x0,0x0,0x0,0x0,0x0,0x3f4fbf73,0xbf163e9e,0x3e9e3f16,0xbf733f4f,
0x3e9ebf16,0xbf733f4f,0x3f4fbf73,0x3f163e9e,0x0,0x0,0x0,0x0,0x0,0x0,0x0,0x0,
0xbf803f80,0x0,0x3f4f3e9e,0xbf163f73,0xbf803f80,0x0,0xbe9ebf4f,0x3f73bf16,0x0,0x0,0x0,0x0,
0x0,0x0,0x0,0x0,0x0,0x3f80bf80,0xbf163f73,0xbf4fbe9e,0x0,0x3f80bf80,0x3f73bf16,0x3e9e3f4f,
0x0,0x0,0x0,0x0,0x0,0x0,0x0,0x0,0xbf163e9e,0x3f4fbf73,0x3f80,0xbf800000,
0xbf733f4f,0x3e9ebf16,0xbf80,0x3f800000,0x0,0x0,0x0,0x0,0x0,0x0,0x0,0x0,
0x3f4fbf73,0x3f16be9e,0xbf800000,0x8000bf80,0x3e9ebf16,0x3f73bf4f,0x3f800000,0x80003f80,0x0,0x0,0x0,0x0,
0x0,0x0,0x0,0x0,0xbf4f3e9e,0xbf16bf73,0x3f7d3f80,0x3e203e9e,0x3e9ebf4f,0x3f733f16,0x3f643f73,0xbe200000,
0x0,0x0,0x3f353f4f,0xbee8be9e,0x0,0x0,0x3ee83f16,0xbf35bf16,0xbf16bf73,0x3f4fbe9e,0xbe208000,0xbf7dbf73,
0x3f733f16,0xbe9e3f4f,0xbee8be9e,0xbf7dbf80,0x0,0x0,0xbf35bf16,0xbf64bf73,0x0,0x0,0xbf64bf4f,0xbf35bf4f,
0xbf73bf4f,0x3e9ebf16,0x3f643f80,0xbee8bf4f,0x3f16be9e,0x3f4f3f73,0x3e203f16,0x3ee80000,0x0,0x0,0xbf35be9e,0x3f7d3f4f,
0x0,0x0,0xbf7dbf73,0x3f353f73,0x3e9ebf16,0x3f733f4f,0xbee88000,0x3f643f16,0x3f4f3f73,0xbf163e9e,0xbf7dbf4f,0x3f643f80,
0x0,0x0,0xbf35bf73,0x3e203f16,0x0,0x0,0x3e20be9e,0xbf35be9e,0xbe9ebf4f,0x3f733f16,0x3f353f80,0x3f353f80,
0x3f4f3e9e,0x3f163f73,0xbf350000,0xbf350000,0x0,0x0,0xbf35bf80,0xbf35bf80,0x0,0x0,0x3f350000,0x3f350000,
0x3f733f16,0x3e9e3f4f,0xbf358000,0xbf358000,0x3f163f73,0xbf4fbe9e,0xbf35bf80,0xbf35bf80,0x0,0x0,0x3f358000,0x3f358000,
0x0,0x0,0x3f353f80,0x3f353f80,0x3f163e9e,0x3f4f3f73,0x3ee83f80,0xbf64bf4f,0x3f733f4f,0x3e9e3f16,0xbf7dbf16,0x3f640000,
0x0,0x0,0x3f35be9e,0xbe203f4f,0x0,0x0,0x3e203f73,0xbf35bf73,0x3f4f3f73,0xbf16be9e,0xbf648000,0x3ee8bf16,
0x3e9e3f16,0xbf73bf4f,0x3e20bf4f,0x3ee83f80,0x0,0x0,0x3f353f73,0xbf7dbf16,0x0,0x0,0xbf7dbe9e,0x3f35be9e,
0xbf64bf4f,0x3e203f80,0x3f7d3e9e,0x3ee8bf4f,0xbf7dbf73,0xbee8bf73,0xbf7d0000,0xbe203f73,0x0,0x3f353f4f,0x3f64be9e,0x0,
0x0,0xbf64bf16,0xbf353f16,0x0,0xbee8bf16,0xbf7d8000,0xbe203f73,0x3f643f16,0xbe20be9e,0x3f64be9e,0xbe20bf80,0xbf7dbe9e,
0x0,0xbf353f16,0x3ee83f73,0x0,0x0,0x3ee8bf4f,0xbf35bf4f,0x0,0xbe203e9e,0xbe203f80,0xbf7d3e9e,0xbee8bf4f,
0xbf64bf16,0x3ee8bf73,0x3f7d0000,0x3e203f73,0x0,0xbf353f4f,0xbf64be9e,0x0,0x0,0x3f64bf16,0x3f353f16,0x0,
0xbf7dbf73,0xbf7d8000,0xbe20bf73,0x3f64bf16,0xbee8bf4f,0x3f643e9e,0xbe203f80,0xbf7d3e9e,0x0,0xbf35bf16,0x3ee8bf73,0x0,
0x0,0x3ee83f4f,0xbf353f4f,0x0,0x3f353f80,0xbee83f80,0x3f64bf4f,0xbf7d3e9e,0xbf350000,0x3f7dbf16,0xbf640000,0x3ee83f16,
0x0,0xbf35be9e,0x3e203f4f,0x0,0x0,0xbe203f73,0x3f35bf73,0x0,0xbf358000,0xbf648000,0x3ee83f16,0x3e20bf73,
0xbf35bf80,0x3e203f4f,0x3ee8bf80,0xbf643f4f,0x0,0x3f35bf73,0xbf7d3f16,0x0,0x0,0xbf7d3e9e,0x3f353e9e,0x0,
0x3f7d3e9e,0xbf353f80,0xbf353f80,0xbf353f80,0xbee83f16,0x3f350000,0x3f350000,0x3f350000,0x0,0x3f35bf80,0x3f35bf80,0x0,
0x0,0xbf350000,0xbf350000,0x0,0x3e203f73,0xbf358000,0xbf358000,0xbf358000,0xbf64bf4f,0xbf353f80,0xbf353f80,0xbf353f80,
0x0,0x3f358000,0x3f358000,0x0,0x0,0x3f35bf80,0x3f35bf80,0x0,0xbf643f80,0x3ee8bf4f,0x3e203e9e,0x0,
0xbe203f16,0xbee80000,0x3f64bf16,0x0,0x3f35be9e,0xbf7d3f4f,0x0,0x0,0x3f7dbf73,0xbf353f73,0x0,0x0,
0xbee88000,0x3f64bf16,0xbf7d3f73,0x0,0xbf7d3f4f,0x3f64bf80,0xbee83f4f,0x0,0xbf353f73,0x3e20bf16,0x0,0x0,
0x3e203e9e,0xbf353e9e,0x0,0x0,0xbf7d3f80,0xbe203e9e,0x3f64bf4f,0x0,0xbf643f73,0x3e200000,0x3f7dbf73,0x0,
0xbf353f4f,0x3ee8be9e,0x0,0x0,0xbee83f16,0x3f35bf16,0x0,0x0,0xbe208000,0xbf7d3f73,0xbee83f16,0x0,
0xbee83e9e,0xbf7d3f80,0xbe203e9e,0x0,0xbf353f16,0xbf643f73,0x0,0x0,0xbf643f4f,0xbf353f4f,0x0,0x0,
0x0,0x0,0x0,0x0,0x0,0x0,0x0,0x0,0x0,0x0,0x0,0x0,
0x0,0x0,0x0,0x0,0x0,0x0,0x0,0x0,0x0,0x0,0x0,0x0,
0x0,0x0,0x0,0x0,0x0,0x0,0x0,0x0,0x0,0x0,0x0,0x0,
0x0,0x0,0x0,0x0,0x0,0x0,0x0,0x0,0x0,0x0,0x0,0x0,
0x0,0x0,0x0,0x0,0x0,0x0,0x0,0x0,0x0,0x0,0x0,0x0,
0x0,0x0,0x0,0x0,
};
__device__ __align__(1024) const uint32_t c_T3[2176] = {
0x3f803f80,0x3f80,0x3f803f80,0x3f80,0x3f803f80,0xbf80,0x3f803f80,0xbf80,0x3f803f80,0x3f80,0x3f803f80,0x3f80,
0x3f803f80,0xbf80,0x3f803f80,0xbf80,0x3f7b3f80,0xbe483f80,0xbe480000,0xbf7b0000,0x3f553f6d,0x3f0ebf6d,0xbf0ebec4,0x3f553ec4,
0x3f0e3f35,0xbf553f35,0xbf55bf35,0xbf0ebf35,0x3e483ec4,0x3f7bbec4,0xbf7bbf6d,0x3e483f6d,0x3f6d3f80,0xbec43f80,0xbf6dbf80,0x3ec4bf80,
0x3ec43f35,0x3f6dbf35,0xbec4bf35,0xbf6d3f35,0xbec40000,0xbf6d0000,0x3ec40000,0x3f6d0000,0xbf6dbf35,0x3ec43f35,0x3f6d3f35,0xbec4bf35,
0x3f553f80,0xbf0e3f80,0x3f0e0000,0x3f550000,0xbe483ec4,0x3f7bbec4,0x3f7b3f6d,0x3e48bf6d,0xbf7bbf35,0xbe48bf35,0x3e483f35,0xbf7b3f35,
0xbf0ebf6d,0xbf553f6d,0xbf55bec4,0x3f0e3ec4,0x3f353f80,0xbf353f80,0x3f353f80,0xbf353f80,0xbf350000,0x3f350000,0xbf350000,0x3f350000,
0xbf35bf80,0x3f35bf80,0xbf35bf80,0x3f35bf80,0x3f350000,0xbf350000,0x3f350000,0xbf350000,0x3f0e3f80,0xbf553f80,0xbf550000,0xbf0e0000,
0xbf7bbec4,0x3e483ec4,0xbe48bf6d,0xbf7b3f6d,0x3e48bf35,0x3f7bbf35,0x3f7b3f35,0xbe483f35,0x3f553f6d,0x3f0ebf6d,0xbf0e3ec4,0x3f55bec4,
0x3ec43f80,0xbf6d3f80,0xbec4bf80,0x3f6dbf80,0xbf6dbf35,0xbec43f35,0x3f6d3f35,0x3ec4bf35,0x3f6d0000,0x3ec40000,0xbf6d0000,0xbec40000,
0xbec43f35,0x3f6dbf35,0x3ec4bf35,0xbf6d3f35,0x3e483f80,0xbf7b3f80,0x3f7b0000,0x3e480000,0xbf0ebf6d,0xbf553f6d,0xbf553ec4,0x3f0ebec4,
0x3f553f35,0xbf0e3f35,0x3f0ebf35,0x3f55bf35,0xbf7bbec4,0xbe483ec4,0xbe483f6d,0x3f7bbf6d,0x3f803f80,0x3f80,0x3f803f80,0x3f80,
0x3f803f80,0xbf80,0x3f803f80,0xbf80,0x3f803f80,0x3f80,0x3f803f80,0x3f80,0x3f803f80,0xbf80,0x3f803f80,0xbf80,
0xbf7bbf80,0x3e48bf80,0x3e480000,0x3f7b0000,0xbf55bf6d,0xbf0e3f6d,0x3f0e3ec4,0xbf55bec4,0xbf0ebf35,0x3f55bf35,0x3f553f35,0x3f0e3f35,
0xbe48bec4,0xbf7b3ec4,0x3f7b3f6d,0xbe48bf6d,0x3f6d3f80,0xbec43f80,0xbf6dbf80,0x3ec4bf80,0x3ec43f35,0x3f6dbf35,0xbec4bf35,0xbf6d3f35,
0xbec40000,0xbf6d0000,0x3ec40000,0x3f6d0000,0xbf6dbf35,0x3ec43f35,0x3f6d3f35,0xbec4bf35,0xbf55bf80,0x3f0ebf80,0xbf0e0000,0xbf550000,
0x3e48bec4,0xbf7b3ec4,0xbf7bbf6d,0xbe483f6d,0x3f7b3f35,0x3e483f35,0xbe48bf35,0x3f7bbf35,0x3f0e3f6d,0x3f55bf6d,0x3f553ec4,0xbf0ebec4,
0x3f353f80,0xbf353f80,0x3f353f80,0xbf353f80,0xbf350000,0x3f350000,0xbf350000,0x3f350000,0xbf35bf80,0x3f35bf80,0xbf35bf80,0x3f35bf80,
0x3f350000,0xbf350000,0x3f350000,0xbf350000,0xbf0ebf80,0x3f55bf80,0x3f550000,0x3f0e0000,0x3f7b3ec4,0xbe48bec4,0x3e483f6d,0x3f7bbf6d,
0xbe483f35,0xbf7b3f35,0xbf7bbf35,0x3e48bf35,0xbf55bf6d,0xbf0e3f6d,0x3f0ebec4,0xbf553ec4,0x3ec43f80,0xbf6d3f80,0xbec4bf80,0x3f6dbf80,
0xbf6dbf35,0xbec43f35,0x3f6d3f35,0x3ec4bf35,0x3f6d0000,0x3ec40000,0xbf6d0000,0xbec40000,0xbec43f35,0x3f6dbf35,0x3ec4bf35,0xbf6d3f35,
0xbe48bf80,0x3f7bbf80,0xbf7b0000,0xbe480000,0x3f0e3f6d,0x3f55bf6d,0x3f55bec4,0xbf0e3ec4,0xbf55bf35,0x3f0ebf35,0xbf0e3f35,0xbf553f35,
0x3f7b3ec4,0x3e48bec4,0x3e48bf6d,0xbf7b3f6d,0xbf803f80,0x3f80,0xbf803f80,0x3f80,0xbf803f80,0xbf80,0xbf803f80,0xbf80,
0xbf803f80,0x3f80,0xbf803f80,0x3f80,0xbf803f80,0xbf80,0xbf803f80,0xbf80,0xbf7b3f80,0x3e483f80,0x3e480000,0x3f7b0000,
0xbf553f6d,0xbf0ebf6d,0x3f0ebec4,0xbf553ec4,0xbf0e3f35,0x3f553f35,0x3f55bf35,0x3f0ebf35,0xbe483ec4,0xbf7bbec4,0x3f7bbf6d,0xbe483f6d,
0xbf6d3f80,0x3ec43f80,0x3f6dbf80,0xbec4bf80,0xbec43f35,0xbf6dbf35,0x3ec4bf35,0x3f6d3f35,0x3ec40000,0x3f6d0000,0xbec40000,0xbf6d0000,
0x3f6dbf35,0xbec43f35,0xbf6d3f35,0x3ec4bf35,0xbf553f80,0x3f0e3f80,0xbf0e0000,0xbf550000,0x3e483ec4,0xbf7bbec4,0xbf7b3f6d,0xbe48bf6d,
0x3f7bbf35,0x3e48bf35,0xbe483f35,0x3f7b3f35,0x3f0ebf6d,0x3f553f6d,0x3f55bec4,0xbf0e3ec4,0xbf353f80,0x3f353f80,0xbf353f80,0x3f353f80,
0x3f350000,0xbf350000,0x3f350000,0xbf350000,0x3f35bf80,0xbf35bf80,0x3f35bf80,0xbf35bf80,0xbf350000,0x3f350000,0xbf350000,0x3f350000,
0xbf0e3f80,0x3f553f80,0x3f550000,0x3f0e0000,0x3f7bbec4,0xbe483ec4,0x3e48bf6d,0x3f7b3f6d,0xbe48bf35,0xbf7bbf35,0xbf7b3f35,0x3e483f35,
0xbf553f6d,0xbf0ebf6d,0x3f0e3ec4,0xbf55bec4,0xbec43f80,0x3f6d3f80,0x3ec4bf80,0xbf6dbf80,0x3f6dbf35,0x3ec43f35,0xbf6d3f35,0xbec4bf35,
0xbf6d0000,0xbec40000,0x3f6d0000,0x3ec40000,0x3ec43f35,0xbf6dbf35,0xbec4bf35,0x3f6d3f35,0xbe483f80,0x3f7b3f80,0xbf7b0000,0xbe480000,
0x3f0ebf6d,0x3f553f6d,0x3f553ec4,0xbf0ebec4,0xbf553f35,0x3f0e3f35,0xbf0ebf35,0xbf55bf35,0x3f7bbec4,0x3e483ec4,0x3e483f6d,0xbf7bbf6d,
0xbf803f80,0x3f80,0xbf803f80,0x3f80,0xbf803f80,0xbf80,0xbf803f80,0xbf80,0xbf803f80,0x3f80,0xbf803f80,0x3f80,
0xbf803f80,0xbf80,0xbf803f80,0xbf80,0x3f7bbf80,0xbe48bf80,0xbe480000,0xbf7b0000,0x3f55bf6d,0x3f0e3f6d,0xbf0e3ec4,0x3f55bec4,
0x3f0ebf35,0xbf55bf35,0xbf553f35,0xbf0e3f35,0x3e48bec4,0x3f7b3ec4,0xbf7b3f6d,0x3e48bf6d,0xbf6d3f80,0x3ec43f80,0x3f6dbf80,0xbec4bf80,
0xbec43f35,0xbf6dbf35,0x3ec4bf35,0x3f6d3f35,0x3ec40000,0x3f6d0000,0xbec40000,0xbf6d0000,0x3f6dbf35,0xbec43f35,0xbf6d3f35,0x3ec4bf35,
0x3f55bf80,0xbf0ebf80,0x3f0e0000,0x3f550000,0xbe48bec4,0x3f7b3ec4,0x3f7bbf6d,0x3e483f6d,0xbf7b3f35,0xbe483f35,0x3e48bf35,0xbf7bbf35,
0xbf0e3f6d,0xbf55bf6d,0xbf553ec4,0x3f0ebec4,0xbf353f80,0x3f353f80,0xbf353f80,0x3f353f80,0x3f350000,0xbf350000,0x3f350000,0xbf350000,
0x3f35bf80,0xbf35bf80,0x3f35bf80,0xbf35bf80,0xbf350000,0x3f350000,0xbf350000,0x3f350000,0x3f0ebf80,0xbf55bf80,0xbf550000,0xbf0e0000,
0xbf7b3ec4,0x3e48bec4,0xbe483f6d,0xbf7bbf6d,0x3e483f35,0x3f7b3f35,0x3f7bbf35,0xbe48bf35,0x3f55bf6d,0x3f0e3f6d,0xbf0ebec4,0x3f553ec4,
0xbec43f80,0x3f6d3f80,0x3ec4bf80,0xbf6dbf80,0x3f6dbf35,0x3ec43f35,0xbf6d3f35,0xbec4bf35,0xbf6d0000,0xbec40000,0x3f6d0000,0x3ec40000,
0x3ec43f35,0xbf6dbf35,0xbec4bf35,0x3f6d3f35,0x3e48bf80,0xbf7bbf80,0x3f7b0000,0x3e480000,0xbf0e3f6d,0xbf55bf6d,0xbf55bec4,0x3f0e3ec4,
0x3f55bf35,0xbf0ebf35,0x3f0e3f35,0x3f553f35,0xbf7b3ec4,0xbe48bec4,0xbe48bf6d,0x3f7b3f6d,0x0,0x3f800000,0x0,0x3f800000,
0x0,0xbf800000,0x0,0xbf800000,0x0,0x3f800000,0x0,0x3f800000,0x0,0xbf800000,0x0,0xbf800000,
0x3e480000,0x3f7b0000,0x3f7b3f80,0xbe483f80,0x3f0e3ec4,0xbf55bec4,0x3f553f6d,0x3f0ebf6d,0x3f553f35,0x3f0e3f35,0x3f0e3f35,0xbf553f35,
0x3f7b3f6d,0xbe48bf6d,0x3e483ec4,0x3f7bbec4,0x3ec40000,0x3f6d0000,0xbec40000,0xbf6d0000,0x3f6d3f35,0xbec4bf35,0xbf6dbf35,0x3ec43f35,
0x3f6d3f80,0xbec43f80,0xbf6dbf80,0x3ec4bf80,0x3ec43f35,0x3f6dbf35,0xbec4bf35,0xbf6d3f35,0x3f0e0000,0x3f550000,0xbf55bf80,0x3f0ebf80,
0x3f7b3f6d,0x3e48bf6d,0x3e48bec4,0xbf7b3ec4,0x3e483f35,0xbf7b3f35,0x3f7b3f35,0x3e483f35,0xbf55bec4,0x3f0e3ec4,0x3f0e3f6d,0x3f55bf6d,
0x3f350000,0x3f350000,0x3f350000,0x3f350000,0x3f353f80,0x3f35bf80,0x3f353f80,0x3f35bf80,0xbf350000,0xbf350000,0xbf350000,0xbf350000,
0xbf35bf80,0xbf353f80,0xbf35bf80,0xbf353f80,0x3f550000,0x3f0e0000,0x3f0e3f80,0xbf553f80,0x3e483f6d,0x3f7bbf6d,0xbf7bbec4,0x3e483ec4,
0xbf7bbf35,0x3e48bf35,0x3e48bf35,0x3f7bbf35,0x3f0ebec4,0xbf553ec4,0x3f553f6d,0x3f0ebf6d,0x3f6d0000,0x3ec40000,0xbf6d0000,0xbec40000,
0xbec43f35,0x3f6dbf35,0x3ec4bf35,0xbf6d3f35,0xbec4bf80,0x3f6dbf80,0x3ec43f80,0xbf6d3f80,0x3f6d3f35,0x3ec4bf35,0xbf6dbf35,0xbec43f35,
0x3f7b0000,0x3e480000,0xbe48bf80,0x3f7bbf80,0xbf553ec4,0x3f0ebec4,0x3f0e3f6d,0x3f55bf6d,0x3f0ebf35,0x3f55bf35,0xbf55bf35,0x3f0ebf35,
0xbe483f6d,0x3f7bbf6d,0x3f7b3ec4,0x3e48bec4,0x0,0x3f800000,0x0,0x3f800000,0x0,0xbf800000,0x0,0xbf800000,
0x0,0x3f800000,0x0,0x3f800000,0x0,0xbf800000,0x0,0xbf800000,0xbe480000,0xbf7b0000,0xbf7bbf80,0x3e48bf80,
0xbf0ebec4,0x3f553ec4,0xbf55bf6d,0xbf0e3f6d,0xbf55bf35,0xbf0ebf35,0xbf0ebf35,0x3f55bf35,0xbf7bbf6d,0x3e483f6d,0xbe48bec4,0xbf7b3ec4,
0x3ec40000,0x3f6d0000,0xbec40000,0xbf6d0000,0x3f6d3f35,0xbec4bf35,0xbf6dbf35,0x3ec43f35,0x3f6d3f80,0xbec43f80,0xbf6dbf80,0x3ec4bf80,
0x3ec43f35,0x3f6dbf35,0xbec4bf35,0xbf6d3f35,0xbf0e0000,0xbf550000,0x3f553f80,0xbf0e3f80,0xbf7bbf6d,0xbe483f6d,0xbe483ec4,0x3f7bbec4,
0xbe48bf35,0x3f7bbf35,0xbf7bbf35,0xbe48bf35,0x3f553ec4,0xbf0ebec4,0xbf0ebf6d,0xbf553f6d,0x3f350000,0x3f350000,0x3f350000,0x3f350000,
0x3f353f80,0x3f35bf80,0x3f353f80,0x3f35bf80,0xbf350000,0xbf350000,0xbf350000,0xbf350000,0xbf35bf80,0xbf353f80,0xbf35bf80,0xbf353f80,
0xbf550000,0xbf0e0000,0xbf0ebf80,0x3f55bf80,0xbe48bf6d,0xbf7b3f6d,0x3f7b3ec4,0xbe48bec4,0x3f7b3f35,0xbe483f35,0xbe483f35,0xbf7b3f35,
0xbf0e3ec4,0x3f55bec4,0xbf55bf6d,0xbf0e3f6d,0x3f6d0000,0x3ec40000,0xbf6d0000,0xbec40000,0xbec43f35,0x3f6dbf35,0x3ec4bf35,0xbf6d3f35,
0xbec4bf80,0x3f6dbf80,0x3ec43f80,0xbf6d3f80,0x3f6d3f35,0x3ec4bf35,0xbf6dbf35,0xbec43f35,0xbf7b0000,0xbe480000,0x3e483f80,0xbf7b3f80,
0x3f55bec4,0xbf0e3ec4,0xbf0ebf6d,0xbf553f6d,0xbf0e3f35,0xbf553f35,0x3f553f35,0xbf0e3f35,0x3e48bf6d,0xbf7b3f6d,0xbf7bbec4,0xbe483ec4,
0x0,0xbf800000,0x0,0xbf800000,0x0,0x3f800000,0x0,0x3f800000,0x0,0xbf800000,0x0,0xbf800000,
0x0,0x3f800000,0x0,0x3f800000,0xbe480000,0xbf7b0000,0xbf7b3f80,0x3e483f80,0xbf0e3ec4,0x3f55bec4,0xbf553f6d,0xbf0ebf6d,
0xbf553f35,0xbf0e3f35,0xbf0e3f35,0x3f553f35,0xbf7b3f6d,0x3e48bf6d,0xbe483ec4,0xbf7bbec4,0xbec40000,0xbf6d0000,0x3ec40000,0x3f6d0000,
0xbf6d3f35,0x3ec4bf35,0x3f6dbf35,0xbec43f35,0xbf6d3f80,0x3ec43f80,0x3f6dbf80,0xbec4bf80,0xbec43f35,0xbf6dbf35,0x3ec4bf35,0x3f6d3f35,
0xbf0e0000,0xbf550000,0x3f55bf80,0xbf0ebf80,0xbf7b3f6d,0xbe48bf6d,0xbe48bec4,0x3f7b3ec4,0xbe483f35,0x3f7b3f35,0xbf7b3f35,0xbe483f35,
0x3f55bec4,0xbf0e3ec4,0xbf0e3f6d,0xbf55bf6d,0xbf350000,0xbf350000,0xbf350000,0xbf350000,0xbf353f80,0xbf35bf80,0xbf353f80,0xbf35bf80,
0x3f350000,0x3f350000,0x3f350000,0x3f350000,0x3f35bf80,0x3f353f80,0x3f35bf80,0x3f353f80,0xbf550000,0xbf0e0000,0xbf0e3f80,0x3f553f80,
0xbe483f6d,0xbf7bbf6d,0x3f7bbec4,0xbe483ec4,0x3f7bbf35,0xbe48bf35,0xbe48bf35,0xbf7bbf35,0xbf0ebec4,0x3f553ec4,0xbf553f6d,0xbf0ebf6d,
0xbf6d0000,0xbec40000,0x3f6d0000,0x3ec40000,0x3ec43f35,0xbf6dbf35,0xbec4bf35,0x3f6d3f35,0x3ec4bf80,0xbf6dbf80,0xbec43f80,0x3f6d3f80,
0xbf6d3f35,0xbec4bf35,0x3f6dbf35,0x3ec43f35,0xbf7b0000,0xbe480000,0x3e48bf80,0xbf7bbf80,0x3f553ec4,0xbf0ebec4,0xbf0e3f6d,0xbf55bf6d,
0xbf0ebf35,0xbf55bf35,0x3f55bf35,0xbf0ebf35,0x3e483f6d,0xbf7bbf6d,0xbf7b3ec4,0xbe48bec4,0x0,0xbf800000,0x0,0xbf800000,
0x0,0x3f800000,0x0,0x3f800000,0x0,0xbf800000,0x0,0xbf800000,0x0,0x3f800000,0x0,0x3f800000,
0x3e480000,0x3f7b0000,0x3f7bbf80,0xbe48bf80,0x3f0ebec4,0xbf553ec4,0x3f55bf6d,0x3f0e3f6d,0x3f55bf35,0x3f0ebf35,0x3f0ebf35,0xbf55bf35,
0x3f7bbf6d,0xbe483f6d,0x3e48bec4,0x3f7b3ec4,0xbec40000,0xbf6d0000,0x3ec40000,0x3f6d0000,0xbf6d3f35,0x3ec4bf35,0x3f6dbf35,0xbec43f35,
0xbf6d3f80,0x3ec43f80,0x3f6dbf80,0xbec4bf80,0xbec43f35,0xbf6dbf35,0x3ec4bf35,0x3f6d3f35,0x3f0e0000,0x3f550000,0xbf553f80,0x3f0e3f80,
0x3f7bbf6d,0x3e483f6d,0x3e483ec4,0xbf7bbec4,0x3e48bf35,0xbf7bbf35,0x3f7bbf35,0x3e48bf35,0xbf553ec4,0x3f0ebec4,0x3f0ebf6d,0x3f553f6d,
0xbf350000,0xbf350000,0xbf350000,0xbf350000,0xbf353f80,0xbf35bf80,0xbf353f80,0xbf35bf80,0x3f350000,0x3f350000,0x3f350000,0x3f350000,
0x3f35bf80,0x3f353f80,0x3f35bf80,0x3f353f80,0x3f550000,0x3f0e0000,0x3f0ebf80,0xbf55bf80,0x3e48bf6d,0x3f7b3f6d,0xbf7b3ec4,0x3e48bec4,
0xbf7b3f35,0x3e483f35,0x3e483f35,0x3f7b3f35,0x3f0e3ec4,0xbf55bec4,0x3f55bf6d,0x3f0e3f6d,0xbf6d0000,0xbec40000,0x3f6d0000,0x3ec40000,
0x3ec43f35,0xbf6dbf35,0xbec4bf35,0x3f6d3f35,0x3ec4bf80,0xbf6dbf80,0xbec43f80,0x3f6d3f80,0xbf6d3f35,0xbec4bf35,0x3f6dbf35,0x3ec43f35,
0x3f7b0000,0x3e480000,0xbe483f80,0x3f7b3f80,0xbf55bec4,0x3f0e3ec4,0x3f0ebf6d,0x3f553f6d,0x3f0e3f35,0x3f553f35,0xbf553f35,0x3f0e3f35,
0xbe48bf6d,0x3f7b3f6d,0x3f7bbec4,0x3e483ec4,0x3f800000,0x0,0x3f800000,0x0,0x3f800000,0x0,0x3f800000,0x0,
0x3f800000,0x0,0x3f800000,0x0,0x3f800000,0x0,0x3f800000,0x0,0x3f800000,0x0,0x3f7fcd79,0x3d20cee7,
0x3f7ffcd7,0x3c20d8d2,0x3f7fb10f,0x3d48fb30,0x3f7ff35e,0x3ca0d6d6,0x3f7f8e56,0x3d712283,0x3f7fe394,0x3cf13d4c,0x3f7f654e,0x3d8ca1f2,
0x3f800000,0x0,0x3f7f35f9,0x3da0af2a,0x3f7ff35e,0x3ca0d6d6,0x3f7ec46d,0x3dc8bd36,0x3f7fcd79,0x3d20cee7,0x3f7e39bc,0x3df0b772,
0x3f7f8e56,0x3d712283,0x3f7d95f4,0x3e0c4cf7,0x3f800000,0x0,0x3f7e39bc,0x3df0b772,0x3f7fe394,0x3cf13d4c,0x3f7d3aac,0x3e164083,
0x3f7f8e56,0x3d712283,0x3f7c0361,0x3e3403f1,0x3f7f0059,0x3db4b86a,0x3f7a9421,0x3e519f65,0x3f800000,0x0,0x3f7cd925,0x3e20305b,
0x3f7fcd79,0x3d20cee7,0x3f7b14be,0x3e47c5c2,0x3f7f35f9,0x3da0af2a,0x3f78ed3c,0x3e6f0c4d,0x3f7e39bc,0x3df0b772,0x3f766377,0x3e8afa3e,
0x3f800000,0x0,0x3f7b14be,0x3e47c5c2,0x3f7fb10f,0x3d48fb30,0x3f7853f8,0x3e78cfcc,0x3f7ec46d,0x3dc8bd36,0x3f74fa0b,0x3e94a031,
0x3f7d3aac,0x3e164083,0x3f710908,0x3eac7cd4,0x3f800000,0x0,0x3f78ed3c,0x3e6f0c4d,0x3f7f8e56,0x3d712283,0x3f74fa0b,0x3e94a031,
0x3f7e39bc,0x3df0b772,0x3f702d4f,0x3eb13641,0x3f7c0361,0x3e3403f1,0x3f6a8b4b,0x3ecd2ef3,0x3f800000,0x0,0x3f766377,0x3e8afa3e,
0x3f7f654e,0x3d8ca1f2,0x3f710908,0x3eac7cd4,0x3f7d95f4,0x3e0c4cf7,0x3f6a8b4b,0x3ecd2ef3,0x3f7a9421,0x3e519f65,0x3f62f219,0x3eece91a,
0x3f800000,0x0,0x3f800000,0x0,0x3f800000,0x0,0x3f7f35f9,0x3da0af2a,0x3f800000,0x0,0x3f7cd925,0x3e20305b,
0x3f800000,0x0,0x3f78ed3c,0x3e6f0c4d,0x3f7f35f9,0x3da0af2a,0x3f800000,0x0,0x3f7f0059,0x3db4b86a,0x3f7f0059,0x3db4b86a,
0x3f7ec46d,0x3dc8bd36,0x3f7c0361,0x3e3403f1,0x3f7e8238,0x3ddcbd0d,0x3f770f11,0x3e862210,0x3f7cd925,0x3e20305b,0x3f800000,0x0,
0x3f7c0361,0x3e3403f1,0x3f7ec46d,0x3dc8bd36,0x3f7b14be,0x3e47c5c2,0x3f7b14be,0x3e47c5c2,0x3f7a0d54,0x3e5b73dc,0x3f74fa0b,0x3e94a031,
0x3f78ed3c,0x3e6f0c4d,0x3f800000,0x0,0x3f770f11,0x3e862210,0x3f7e8238,0x3ddcbd0d,0x3f74fa0b,0x3e94a031,0x3f7a0d54,0x3e5b73dc,
0x3f72ae9e,0x3ea2fd52,0x3f72ae9e,0x3ea2fd52,0x3f737871,0x3e9e377a,0x3f800000,0x0,0x3f702d4f,0x3eb13641,0x3f7e39bc,0x3df0b772,
0x3f6c835e,0x3ec3ef15,0x3f78ed3c,0x3e6f0c4d,0x3f687c12,0x3ed65a92,0x3f702d4f,0x3eb13641,0x3f6c835e,0x3ec3ef15,0x3f800000,0x0,
0x3f676bd8,0x3edae880,0x3f7deafa,0x3e0255f4,0x3f61c598,0x3ef15aea,0x3f77b493,0x3e814693,0x3f5b941a,0x3f039c3d,0x3f6d76aa,0x3ebf47d7,
0x3f641901,0x3ee87171,0x3f800000,0x0,0x3f5cdc29,0x3f0172c3,0x3f7d95f4,0x3e0c4cf7,0x3f54db31,0x3f0e39da,0x3f766377,0x3e8afa3e,
0x3f4c1d35,0x3f1a82a4,0x3f6a8b4b,0x3ecd2ef3,0x3f5a46a0,0x3f05c277,0x3f800000,0x0,0x3f50935b,0x3f146eba,0x3f7d3aac,0x3e164083,
0x3f45e403,0x3f226799,0x3f74fa0b,0x3e94a031,0x3f3a4582,0x3f2f9c32,0x3f676bd8,0x3edae880,0x3f737871,0x3e9e377a,0x3f4f1bbd,0x3f167918,
0x3f6c835e,0x3ec3ef15,0x3f42a9f7,0x3f26423a,0x3f641901,0x3ee87171,0x3f3504f3,0x3f3504f3,0x3f5a46a0,0x3f05c277,0x3f26423a,0x3f42a9f7,
0x3f702d4f,0x3eb13641,0x3f42a9f7,0x3f26423a,0x3f676bd8,0x3edae880,0x3f333bc6,0x3f36c9a9,0x3f5cdc29,0x3f0172c3,0x3f226799,0x3f45e403,
0x3f50935b,0x3f146eba,0x3f104f0e,0x3f53731f,0x3f6c835e,0x3ec3ef15,0x3f3504f3,0x3f3504f3,0x3f61c598,0x3ef15aea,0x3f226799,0x3f45e403,
0x3f54db31,0x3f0e39da,0x3f0e39da,0x3f54db31,0x3f45e403,0x3f226799,0x3ef15aea,0x3f61c598,0x3f687c12,0x3ed65a92,0x3f26423a,0x3f42a9f7,
0x3f5b941a,0x3f039c3d,0x3f104f0e,0x3f53731f,0x3f4c1d35,0x3f1a82a4,0x3ef15aea,0x3f61c598,0x3f3a4582,0x3f2f9c32,0x3ebf47d7,0x3f6d76aa,
0x3f641901,0x3ee87171,0x3f167918,0x3f4f1bbd,0x3f54db31,0x3f0e39da,0x3efa2c90,0x3f5f5be6,0x3f42a9f7,0x3f26423a,0x3ec3ef15,0x3f6c835e,
0x3f2dc5e3,0x3f3bfc8f,0x3e8afa3e,0x3f766377,0x3f5f5be6,0x3efa2c90,0x3f05c277,0x3f5a46a0,0x3f4d9f02,0x3f187fc0,0x3ed1c759,0x3f698690,
0x3f3889dc,0x3f316e2c,0x3e94a031,0x3f74fa0b,0x3f207440,0x3f4779bc,0x3e2a1c3f,0x3f7c7160,0x3f5a46a0,0x3f05c277,0x3ee87171,0x3f641901,
0x3f45e403,0x3f226799,0x3ea7bf25,0x3f71decf,0x3f2dc5e3,0x3f3bfc8f,0x3e47c5c2,0x3f7b14be,0x3f1260b2,0x3f5205d4,0x3d712283,0x3f7f8e56,
0x3f54db31,0x3f0e39da,0x3ec3ef15,0x3f6c835e,0x3f3daef9,0x3f2beb4a,0x3e78cfcc,0x3f7853f8,0x3f226799,0x3f45e403,0x3dc8bd36,0x3f7ec46d,
0x3f039c3d,0x3f5b941a,0xbd48fb30,0x3f7fb10f,0x3f800000,0x0,0x3f4f1bbd,0x3f167918,0x3f7cd925,0x3e20305b,0x3f3504f3,0x3f3504f3,
0x3f737871,0x3e9e377a,0x3f167918,0x3f4f1bbd,0x3f641901,0x3ee87171,0x3ee87171,0x3f641901,0x3f800000,0x0,0x3f490a88,0x3f1e7cf1,
0x3f7c7160,0x3e2a1c3f,0x3f2beb4a,0x3f3daef9,0x3f71decf,0x3ea7bf25,0x3f0a04f8,0x3f579b8c,0x3f609384,0x3ef5c6c5,0x3ec8917e,0x3f6b8a3d,
0x3f800000,0x0,0x3f42a9f7,0x3f26423a,0x3f7c0361,0x3e3403f1,0x3f226799,0x3f45e403,0x3f702d4f,0x3eb13641,0x3efa2c90,0x3f5f5be6,
0x3f5cdc29,0x3f0172c3,0x3ea7bf25,0x3f71decf,0x3f800000,0x0,0x3f3bfc8f,0x3f2dc5e3,0x3f7b8f2a,0x3e3de731,0x3f187fc0,0x3f4d9f02,
0x3f6e641a,0x3eba9be1,0x3edf7108,0x3f6655e7,0x3f58f3c4,0x3f07e565,0x3e862210,0x3f770f11,0x3f800000,0x0,0x3f3504f3,0x3f3504f3,
0x3f7b14be,0x3e47c5c2,0x3f0e39da,0x3f54db31,0x3f6c835e,0x3ec3ef15,0x3ec3ef15,0x3f6c835e,0x3f54db31,0x3f0e39da,0x3e47c5c2,0x3f7b14be,
0x3f800000,0x0,0x3f2dc5e3,0x3f3bfc8f,0x3f7a9421,0x3e519f65,0x3f039c3d,0x3f5b941a,0x3f6a8b4b,0x3ecd2ef3,0x3ea7bf25,0x3f71decf,
0x3f50935b,0x3f146eba,0x3e0255f4,0x3f7deafa,0x3f800000,0x0,0x3f26423a,0x3f42a9f7,0x3f7a0d54,0x3e5b73dc,0x3ef15aea,0x3f61c598,
0x3f687c12,0x3ed65a92,0x3e8afa3e,0x3f766377,0x3f4c1d35,0x3f1a82a4,0x3d712283,0x3f7f8e56,0x3f800000,0x0,0x3f1e7cf1,0x3f490a88,
0x3f79805c,0x3e6542e9,0x3edae880,0x3f676bd8,0x3f6655e7,0x3edf7108,0x3e5b73dc,0x3f7a0d54,0x3f4779bc,0x3f207440,0xbc20d8d2,0x3f7ffcd7,
0x3e9e377a,0x3f737871,0x3f800000,0x0,0x3e20305b,0x3f7cd925,0x3f78ed3c,0x3e6f0c4d,0x0,0x3f800000,0x3f641901,0x3ee87171,
0xbe20305b,0x3f7cd925,0x3f42a9f7,0x3f26423a,0x3e6f0c4d,0x3f78ed3c,0x3f800000,0x0,0x3d8ca1f2,0x3f7f654e,0x3f7853f8,0x3e78cfcc,
0xbdc8bd36,0x3f7ec46d,0x3f61c598,0x3ef15aea,0xbe862210,0x3f770f11,0x3f3daef9,0x3f2beb4a,0x3e20305b,0x3f7cd925,0x3f800000,0x0,
0xbca0d6d6,0x3f7ff35e,0x3f77b493,0x3e814693,0xbe47c5c2,0x3f7b14be,0x3f5f5be6,0x3efa2c90,0xbeba9be1,0x3f6e641a,0x3f3889dc,0x3f316e2c,
0x3da0af2a,0x3f7f35f9,0x3f800000,0x0,0xbddcbd0d,0x3f7e8238,0x3f770f11,0x3e862210,0xbe94a031,0x3f74fa0b,0x3f5cdc29,0x3f0172c3,
0xbeece91a,0x3f62f219,0x3f333bc6,0x3f36c9a9,0x0,0x3f800000,0x3f800000,0x0,0xbe47c5c2,0x3f7b14be,0x3f766377,0x3e8afa3e,
0xbec3ef15,0x3f6c835e,0x3f5a46a0,0x3f05c277,0xbf0e39da,0x3f54db31,0x3f2dc5e3,0x3f3bfc8f,0xbda0af2a,0x3f7f35f9,0x3f800000,0x0,
0xbe8fcefe,0x3f75b1c9,0x3f75b1c9,0x3e8fcefe,0xbef15aea,0x3f61c598,0x3f579b8c,0x3f0a04f8,0xbf2456f1,0x3f444969,0x3f28296a,0x3f4105b8,
0xbe20305b,0x3f7cd925,0x3f800000,0x0,0xbeba9be1,0x3f6e641a,0x3f74fa0b,0x3e94a031,0xbf0e39da,0x3f54db31,0x3f54db31,0x3f0e39da,
0xbf3889dc,0x3f316e2c,0x3f226799,0x3f45e403,0xbe6f0c4d,0x3f78ed3c,0x3f800000,0x0,0xbee3f40d,0x3f653a48,0x3f743c41,0x3e996dba,
0xbf226799,0x3f45e403,0x3f5205d4,0x3f1260b2,0xbf4a965e,0x3f1c81b9,0x3f1c81b9,0x3f4a965e,0x3f167918,0x3f4f1bbd,0xbe9e377a,0x3f737871,
0x3ec3ef15,0x3f6c835e,0xbf05c277,0x3f5a46a0,0x3e20305b,0x3f7cd925,0xbf3504f3,0x3f3504f3,0xbda0af2a,0x3f7f35f9,0xbf5a46a0,0x3f05c277,
0x3f0e39da,0x3f54db31,0xbec3ef15,0x3f6c835e,0x3eac7cd4,0x3f710908,0xbf187fc0,0x3f4d9f02,0x3dc8bd36,0x3f7ec46d,0xbf45e403,0x3f226799,
0xbe164083,0x3f7d3aac,0xbf676bd8,0x3edae880,0x3f05c277,0x3f5a46a0,0xbee87171,0x3f641901,0x3e94a031,0x3f74fa0b,0xbf2a0c73,0x3f3f5cb5,
0x3d20cee7,0x3f7fcd79,0xbf54db31,0x3f0e39da,0xbe5b73dc,0x3f7a0d54,0xbf71decf,0x3ea7bf25,0x3efa2c90,0x3f5f5be6,0xbf05c277,0x3f5a46a0,
0x3e78cfcc,0x3f7853f8,0xbf3a4582,0x3f2f9c32,0xbca0d6d6,0x3f7ff35e,0xbf61c598,0x3ef15aea,0xbe8fcefe,0x3f75b1c9,0xbf79805c,0x3e6542e9,
0x3ee87171,0x3f641901,0xbf167918,0x3f4f1bbd,0x3e47c5c2,0x3f7b14be,0xbf490a88,0x3f1e7cf1,0xbda0af2a,0x3f7f35f9,0xbf6c835e,0x3ec3ef15,
0xbeb13641,0x3f702d4f,0xbf7e39bc,0x3df0b772,0x3ed65a92,0x3f687c12,0xbf26423a,0x3f42a9f7,0x3e164083,0x3f7d3aac,0xbf563e03,0x3f0c2124,
0xbe0c4cf7,0x3f7d95f4,0xbf74fa0b,0x3e94a031,0xbed1c759,0x3f698690,0xbf7ffcd7,0x3c20d8d2,0x3ec3ef15,0x3f6c835e,0xbf3504f3,0x3f3504f3,
0x3dc8bd36,0x3f7ec46d,0xbf61c598,0x3ef15aea,0xbe47c5c2,0x3f7b14be,0xbf7b14be,0x3e47c5c2,0xbef15aea,0x3f61c598,0xbf7ec46d,0xbdc8bd36,
0x3eb13641,0x3f702d4f,0xbf42a9f7,0x3f26423a,0x3d48fb30,0x3f7fb10f,0xbf6b8a3d,0x3ec8917e,0xbe814693,0x3f77b493,0xbf7ec46d,0x3dc8bd36,
0xbf07e565,0x3f58f3c4,0xbf7a9421,0xbe519f65,0x80003f80,0x80003f80,0x80004000,0x3f96bfcf,0x80004000,0xbf96bfcf,0x80004000,0x80004000,
0x80004000,0x3ff33f1e,0x80004000,0xbf96bfcf,0x80004000,0xbff33f1e,0x80004000,0x3ff33f1e,0x80003f80,0x80003f80,0xbff33f1e,0x3ff33f1e,
0xbf1e3ff3,0xbf1ebff3,0xc0000000,0xc0000000,0xbf963fcf,0x3f963fcf,0xbff3bf1e,0x3ff3bf1e,0xbfcf3f96,0xbfcfbf96,0xbfcfbf96,0xbfcf3f96,
0x80003f80,0x80003f80,0xbf96bfcf,0x80004000,0xbf963fcf,0x8000c000,0x8000c000,0x8000c000,0xbff33f1e,0x80004000,0x3f96bfcf,0x80004000,
0xbff3bf1e,0x8000c000,0x3ff3bf1e,0x8000c000,0x80003f80,0x80003f80,0x3f96bfcf,0xbff33f1e,0xbfcf3f96,0x3f1ebff3,0x40000000,0x40000000,
0xbff3bf1e,0xbf963fcf,0x3f963fcf,0xbff3bf1e,0xbf1ebff3,0x3fcfbf96,0xbf1e3ff3,0x3fcf3f96,0x80003f80,0x80003f80,0x3ff33f1e,0xbf96bfcf,
0xbff33f1e,0x3f96bfcf,0x80004000,0x80004000,0xbf96bfcf,0xbff33f1e,0xbff33f1e,0x3f96bfcf,0x3f96bfcf,0x3ff33f1e,0xbf96bfcf,0xbff33f1e,
0x80003f80,0x80003f80,0x80004000,0x3f96bfcf,0xc0000000,0x3fcfbf96,0xc0000000,0xc0000000,0x8000c000,0xbff3bf1e,0x8000c000,0x3f963fcf,
0x40000000,0x3f1e3ff3,0x40000000,0x3f1ebff3,0x80003f80,0x80003f80,0xbff33f1e,0x3ff33f1e,0xbff3bf1e,0x3ff3bf1e,0x8000c000,0x8000c000,
0x3f96bfcf,0xbf96bfcf,0x3ff33f1e,0xbff33f1e,0x3f963fcf,0xbf963fcf,0xbf963fcf,0x3f963fcf,0x80003f80,0x80003f80,0xbf96bfcf,0x80004000,
0xbfcfbf96,0x40000000,0x40000000,0x40000000,0x3ff3bf1e,0x8000c000,0xbf963fcf,0x8000c000,0xbf1e3ff3,0xc0000000,0xbf1ebff3,0xc0000000,
0x80004000,0xbff33f1e,0x80003f80,0x0,0x80004000,0x3f96bfcf,0x3ff33f1e,0x0,0x80003f80,0x80003f80,0x3f96bfcf,0x0,
0x0,0x0,0xbf96bfcf,0x0,0xbf96bfcf,0x3f96bfcf,0x80003f80,0x0,0xbf1ebff3,0xbf1e3ff3,0x3fcf3f96,0x0,
0x8000bf80,0x8000bf80,0x3ff3bf1e,0x0,0x0,0x0,0x3f1ebff3,0x0,0x3ff33f1e,0x80004000,0x80003f80,0x0,
0x3f963fcf,0x8000c000,0x3f963fcf,0x0,0x80003f80,0x80003f80,0x3ff33f1e,0x0,0x0,0x0,0x3ff3bf1e,0x0,
0xbff33f1e,0xbf96bfcf,0x80003f80,0x0,0xbfcfbf96,0x3f1e3ff3,0x3f1e3ff3,0x0,0x8000bf80,0x8000bf80,0x3f963fcf,0x0,
0x0,0x0,0x3fcf3f96,0x0,0x3f96bfcf,0x3ff33f1e,0x0,0x0,0x3ff33f1e,0xbf96bfcf,0x0,0x0,
0x80003f80,0x80003f80,0x0,0x0,0x0,0x0,0x0,0x0,0x80004000,0xbff33f1e,0x0,0x0,
0xc0000000,0x3fcf3f96,0x0,0x0,0x8000bf80,0x8000bf80,0x0,0x0,0x0,0x0,0x0,0x0,
0xbf96bfcf,0x3f96bfcf,0x0,0x0,0x3ff3bf1e,0xbff3bf1e,0x0,0x0,0x80003f80,0x80003f80,0x0,0x0,
0x0,0x0,0x0,0x0,0x3ff33f1e,0x80004000,0x0,0x0,0xbfcf3f96,0x40000000,0x0,0x0,
0x8000bf80,0x8000bf80,0x0,0x0,0x0,0x0,0x0,0x0,0xbff33f1e,0x0,0xbf96bfcf,0x0,
0x80004000,0x0,0xbff33f1e,0x0,0x3ff33f1e,0x0,0x80003f80,0x0,0x3f96bfcf,0x0,0x0,0x0,
0xbf96bfcf,0x0,0x3ff33f1e,0x0,0xc0000000,0x0,0x3fcfbf96,0x0,0xbf963fcf,0x0,0x8000bf80,0x0,
0x3f1e3ff3,0x0,0x0,0x0,0x3f96bfcf,0x0,0xbff33f1e,0x0,0x8000c000,0x0,0xbf963fcf,0x0,
0xbf96bfcf,0x0,0x80003f80,0x0,0xbff3bf1e,0x0,0x0,0x0,0x3ff33f1e,0x0,0x3f96bfcf,0x0,
0x40000000,0x0,0x3f1ebff3,0x0,0x3ff3bf1e,0x0,0x8000bf80,0x0,0x3fcfbf96,0x0,0x0,0x0,
0x0,0x0,0x0,0x0,0x0,0x0,0x0,0x0,0x0,0x0,0x0,0x0,
0x0,0x0,0x0,0x0,0x0,0x0,0x0,0x0,0x0,0x0,0x0,0x0,
0x0,0x0,0x0,0x0,0x0,0x0,0x0,0x0,0x0,0x0,0x0,0x0,
0x0,0x0,0x0,0x0,0x0,0x0,0x0,0x0,0x0,0x0,0x0,0x0,
0x0,0x0,0x0,0x0,0x0,0x0,0x0,0x0,0x0,0x0,0x0,0x0,
0x0,0x0,0x0,0x0,
};
__device__ __align__(1024) const uint32_t c_T2S[6144] = {
0x3f803f80,0x3f803f80,0x3f803f80,0x3f803f80,0x3f803f80,0x3f803f80,0x3f803f80,0x3f803f80,0x3f803f80,0x3f803f80,0x3f803f80,0x3f803f80,
0x3f803f80,0x3f803f80,0x3f803f80,0x3f803f80,0x3f803f80,0x3f803f80,0x3f803f80,0x3f803f80,0x3f803f80,0x3f803f80,0x3f803f80,0x3f803f80,
0x3f803f80,0x3f803f80,0x3f803f80,0x3f803f80,0x3f803f80,0x3f803f80,0x3f803f80,0x3f803f80,0x3f223f35,0x3ef13f0e,0x3e953ec4,0x3dc93e48,
0x3f7f3f80,0x3f753f7b,0x3f623f6d,0x3f463f55,0xbf46bf35,0xbf62bf55,0xbf75bf6d,0xbf7fbf7b,0xbdc90000,0xbe95be48,0xbef1bec4,0xbf22bf0e,
0xbf22bf35,0xbef1bf0e,0xbe95bec4,0xbdc9be48,0xbf7fbf80,0xbf75bf7b,0xbf62bf6d,0xbf46bf55,0x3f463f35,0x3f623f55,0x3f753f6d,0x3f7f3f7b,
0x3dc90000,0x3e953e48,0x3ef13ec4,0x3f223f0e,0xbf7bbf80,0xbf55bf6d,0xbf0ebf35,0xbe48bec4,0x3e480000,0x3f0e3ec4,0x3f553f35,0x3f7b3f6d,
0x3f7b3f80,0x3f553f6d,0x3f0e3f35,0x3e483ec4,0xbe480000,0xbf0ebec4,0xbf55bf35,0xbf7bbf6d,0xbf7bbf80,0xbf55bf6d,0xbf0ebf35,0xbe48bec4,
0x3e480000,0x3f0e3ec4,0x3f553f35,0x3f7b3f6d,0x3f7b3f80,0x3f553f6d,0x3f0e3f35,0x3e483ec4,0xbe480000,0xbf0ebec4,0xbf55bf35,0xbf7bbf6d,
0x3ef13f35,0xbdc93e48,0xbf22bec4,0xbf75bf55,0x3e950000,0x3f463f0e,0x3f7f3f6d,0x3f623f7b,0xbf62bf35,0xbf7fbf7b,0xbf46bf6d,0xbe95bf0e,
0x3f753f80,0x3f223f55,0x3dc93ec4,0xbef1be48,0xbef1bf35,0x3dc9be48,0x3f223ec4,0x3f753f55,0xbe950000,0xbf46bf0e,0xbf7fbf6d,0xbf62bf7b,
0x3f623f35,0x3f7f3f7b,0x3f463f6d,0x3e953f0e,0xbf75bf80,0xbf22bf55,0xbdc9bec4,0x3ef13e48,0x3f6d3f80,0x3ec43f35,0xbec40000,0xbf6dbf35,
0xbf6dbf80,0xbec4bf35,0x3ec40000,0x3f6d3f35,0x3f6d3f80,0x3ec43f35,0xbec40000,0xbf6dbf35,0xbf6dbf80,0xbec4bf35,0x3ec40000,0x3f6d3f35,
0x3f6d3f80,0x3ec43f35,0xbec40000,0xbf6dbf35,0xbf6dbf80,0xbec4bf35,0x3ec40000,0x3f6d3f35,0x3f6d3f80,0x3ec43f35,0xbec40000,0xbf6dbf35,
0xbf6dbf80,0xbec4bf35,0x3ec40000,0x3f6d3f35,0x3e953f35,0xbf22be48,0xbf7fbf6d,0xbef1bf55,0xbf62bf80,0xbdc9bf0e,0x3f463ec4,0x3f753f7b,
0xbf75bf35,0xbf46bf7b,0x3dc9bec4,0x3f623f0e,0x3ef10000,0x3f7f3f55,0x3f223f6d,0xbe953e48,0xbe95bf35,0x3f223e48,0x3f7f3f6d,0x3ef13f55,
0x3f623f80,0x3dc93f0e,0xbf46bec4,0xbf75bf7b,0x3f753f35,0x3f463f7b,0xbdc93ec4,0xbf62bf0e,0xbef10000,0xbf7fbf55,0xbf22bf6d,0x3e95be48,
0xbf55bf80,0x3e48bec4,0x3f7b3f35,0x3f0e3f6d,0xbf0e0000,0xbf7bbf6d,0xbe48bf35,0x3f553ec4,0x3f553f80,0xbe483ec4,0xbf7bbf35,0xbf0ebf6d,
0x3f0e0000,0x3f7b3f6d,0x3e483f35,0xbf55bec4,0xbf55bf80,0x3e48bec4,0x3f7b3f35,0x3f0e3f6d,0xbf0e0000,0xbf7bbf6d,0xbe48bf35,0x3f553ec4,
0x3f553f80,0xbe483ec4,0xbf7bbf35,0xbf0ebf6d,0x3f0e0000,0x3f7b3f6d,0x3e483f35,0xbf55bec4,0x3dc93f35,0xbf75bf0e,0xbef1bf6d,0x3f463e48,
0xbf220000,0xbf62bf7b,0x3e95bec4,0x3f7f3f55,0xbf7fbf35,0xbe95bf55,0x3f623ec4,0x3f223f7b,0xbf46bf80,0x3ef1be48,0x3f753f6d,0xbdc93f0e,
0xbdc9bf35,0x3f753f0e,0x3ef13f6d,0xbf46be48,0x3f220000,0x3f623f7b,0xbe953ec4,0xbf7fbf55,0x3f7f3f35,0x3e953f55,0xbf62bec4,0xbf22bf7b,
0x3f463f80,0xbef13e48,0xbf75bf6d,0x3dc9bf0e,0x3f353f80,0xbf350000,0xbf35bf80,0x3f350000,0x3f353f80,0xbf350000,0xbf35bf80,0x3f350000,
0x3f353f80,0xbf350000,0xbf35bf80,0x3f350000,0x3f353f80,0xbf350000,0xbf35bf80,0x3f350000,0x3f353f80,0xbf350000,0xbf35bf80,0x3f350000,
0x3f353f80,0xbf350000,0xbf35bf80,0x3f350000,0x3f353f80,0xbf350000,0xbf35bf80,0x3f350000,0x3f353f80,0xbf350000,0xbf35bf80,0x3f350000,
0xbdc93f35,0xbf75bf55,0x3ef1bec4,0x3f463f7b,0x3f223f80,0xbf62be48,0xbe95bf6d,0x3f7f3f0e,0xbf7fbf35,0x3e95bf0e,0x3f623f6d,0xbf223e48,
0xbf460000,0xbef1bf7b,0x3f753ec4,0x3dc93f55,0x3dc9bf35,0x3f753f55,0xbef13ec4,0xbf46bf7b,0xbf22bf80,0x3f623e48,0x3e953f6d,0xbf7fbf0e,
0x3f7f3f35,0xbe953f0e,0xbf62bf6d,0x3f22be48,0x3f460000,0x3ef13f7b,0xbf75bec4,0xbdc9bf55,0xbf0ebf80,0x3f7b3ec4,0xbe483f35,0xbf55bf6d,
0x3f550000,0x3e483f6d,0xbf7bbf35,0x3f0ebec4,0x3f0e3f80,0xbf7bbec4,0x3e48bf35,0x3f553f6d,0xbf550000,0xbe48bf6d,0x3f7b3f35,0xbf0e3ec4,
0xbf0ebf80,0x3f7b3ec4,0xbe483f35,0xbf55bf6d,0x3f550000,0x3e483f6d,0xbf7bbf35,0x3f0ebec4,0x3f0e3f80,0xbf7bbec4,0x3e48bf35,0x3f553f6d,
0xbf550000,0xbe48bf6d,0x3f7b3f35,0xbf0e3ec4,0xbe953f35,0xbf22bf7b,0x3f7f3ec4,0xbef13f0e,0x3f620000,0xbdc93f55,0xbf46bf6d,0x3f753e48,
0xbf75bf35,0x3f46be48,0x3dc93f6d,0xbf62bf55,0x3ef13f80,0xbf7fbf0e,0x3f22bec4,0x3e953f7b,0x3e95bf35,0x3f223f7b,0xbf7fbec4,0x3ef1bf0e,
0xbf620000,0x3dc9bf55,0x3f463f6d,0xbf75be48,0x3f753f35,0xbf463e48,0xbdc9bf6d,0x3f623f55,0xbef1bf80,0x3f7f3f0e,0xbf223ec4,0xbe95bf7b,
0x3ec43f80,0xbf6dbf35,0x3f6d0000,0xbec43f35,0xbec4bf80,0x3f6d3f35,0xbf6d0000,0x3ec4bf35,0x3ec43f80,0xbf6dbf35,0x3f6d0000,0xbec43f35,
0xbec4bf80,0x3f6d3f35,0xbf6d0000,0x3ec4bf35,0x3ec43f80,0xbf6dbf35,0x3f6d0000,0xbec43f35,0xbec4bf80,0x3f6d3f35,0xbf6d0000,0x3ec4bf35,
0x3ec43f80,0xbf6dbf35,0x3f6d0000,0xbec43f35,0xbec4bf80,0x3f6d3f35,0xbf6d0000,0x3ec4bf35,0xbef13f35,0xbdc9bf7b,0x3f223f6d,0xbf75bf0e,
0xbe95bf80,0x3f463f55,0xbf7fbec4,0x3f62be48,0xbf62bf35,0x3f7f3e48,0xbf463ec4,0x3e95bf55,0x3f750000,0xbf223f0e,0x3dc9bf6d,0x3ef13f7b,
0x3ef1bf35,0x3dc93f7b,0xbf22bf6d,0x3f753f0e,0x3e953f80,0xbf46bf55,0x3f7f3ec4,0xbf623e48,0x3f623f35,0xbf7fbe48,0x3f46bec4,0xbe953f55,
0xbf750000,0x3f22bf0e,0xbdc93f6d,0xbef1bf7b,0xbe48bf80,0x3f0e3f6d,0xbf55bf35,0x3f7b3ec4,0xbf7b0000,0x3f55bec4,0xbf0e3f35,0x3e48bf6d,
0x3e483f80,0xbf0ebf6d,0x3f553f35,0xbf7bbec4,0x3f7b0000,0xbf553ec4,0x3f0ebf35,0xbe483f6d,0xbe48bf80,0x3f0e3f6d,0xbf55bf35,0x3f7b3ec4,
0xbf7b0000,0x3f55bec4,0xbf0e3f35,0x3e48bf6d,0x3e483f80,0xbf0ebf6d,0x3f553f35,0xbf7bbec4,0x3f7b0000,0xbf553ec4,0x3f0ebf35,0xbe483f6d,
0xbf223f35,0x3ef1bf55,0xbe953f6d,0x3dc9bf7b,0xbf7f0000,0x3f75be48,0xbf623ec4,0x3f46bf0e,0xbf46bf35,0x3f623f0e,0xbf75bec4,0x3f7f3e48,
0xbdc9bf80,0x3e953f7b,0xbef1bf6d,0x3f223f55,0x3f22bf35,0xbef13f55,0x3e95bf6d,0xbdc93f7b,0x3f7f0000,0xbf753e48,0x3f62bec4,0xbf463f0e,
0x3f463f35,0xbf62bf0e,0x3f753ec4,0xbf7fbe48,0x3dc93f80,0xbe95bf7b,0x3ef13f6d,0xbf22bf55,0x3f80,0xbf80,0x3f80,0xbf80,
0x3f80,0xbf80,0x3f80,0xbf80,0x3f80,0xbf80,0x3f80,0xbf80,0x3f80,0xbf80,0x3f80,0xbf80,
0x3f80,0xbf80,0x3f80,0xbf80,0x3f80,0xbf80,0x3f80,0xbf80,0x3f80,0xbf80,0x3f80,0xbf80,
0x3f80,0xbf80,0x3f80,0xbf80,0xbf463f35,0x3f62bf0e,0xbf753ec4,0x3f7fbe48,0xbdc93f80,0x3e95bf7b,0xbef13f6d,0x3f22bf55,
0xbf22bf35,0x3ef13f55,0xbe95bf6d,0x3dc93f7b,0xbf7f0000,0x3f753e48,0xbf62bec4,0x3f463f0e,0x3f46bf35,0xbf623f0e,0x3f75bec4,0xbf7f3e48,
0x3dc9bf80,0xbe953f7b,0x3ef1bf6d,0xbf223f55,0x3f223f35,0xbef1bf55,0x3e953f6d,0xbdc9bf7b,0x3f7f0000,0xbf75be48,0x3f623ec4,0xbf46bf0e,
0x3e48bf80,0xbf0e3f6d,0x3f55bf35,0xbf7b3ec4,0x3f7b0000,0xbf55bec4,0x3f0e3f35,0xbe48bf6d,0xbe483f80,0x3f0ebf6d,0xbf553f35,0x3f7bbec4,
0xbf7b0000,0x3f553ec4,0xbf0ebf35,0x3e483f6d,0x3e48bf80,0xbf0e3f6d,0x3f55bf35,0xbf7b3ec4,0x3f7b0000,0xbf55bec4,0x3f0e3f35,0xbe48bf6d,
0xbe483f80,0x3f0ebf6d,0xbf553f35,0x3f7bbec4,0xbf7b0000,0x3f553ec4,0xbf0ebf35,0x3e483f6d,0xbf623f35,0x3f7fbe48,0xbf46bec4,0x3e953f55,
0x3f750000,0xbf22bf0e,0x3dc93f6d,0x3ef1bf7b,0xbef1bf35,0xbdc93f7b,0x3f22bf6d,0xbf753f0e,0xbe953f80,0x3f46bf55,0xbf7f3ec4,0x3f623e48,
0x3f62bf35,0xbf7f3e48,0x3f463ec4,0xbe95bf55,0xbf750000,0x3f223f0e,0xbdc9bf6d,0xbef13f7b,0x3ef13f35,0x3dc9bf7b,0xbf223f6d,0x3f75bf0e,
0x3e95bf80,0xbf463f55,0x3f7fbec4,0xbf62be48,0xbec43f80,0x3f6dbf35,0xbf6d0000,0x3ec43f35,0x3ec4bf80,0xbf6d3f35,0x3f6d0000,0xbec4bf35,
0xbec43f80,0x3f6dbf35,0xbf6d0000,0x3ec43f35,0x3ec4bf80,0xbf6d3f35,0x3f6d0000,0xbec4bf35,0xbec43f80,0x3f6dbf35,0xbf6d0000,0x3ec43f35,
0x3ec4bf80,0xbf6d3f35,0x3f6d0000,0xbec4bf35,0xbec43f80,0x3f6dbf35,0xbf6d0000,0x3ec43f35,0x3ec4bf80,0xbf6d3f35,0x3f6d0000,0xbec4bf35,
0xbf753f35,0x3f463e48,0x3dc9bf6d,0xbf623f55,0x3ef1bf80,0xbf7f3f0e,0x3f223ec4,0x3e95bf7b,0xbe95bf35,0xbf223f7b,0x3f7fbec4,0xbef1bf0e,
0x3f620000,0xbdc9bf55,0xbf463f6d,0x3f75be48,0x3f75bf35,0xbf46be48,0xbdc93f6d,0x3f62bf55,0xbef13f80,0x3f7fbf0e,0xbf22bec4,0xbe953f7b,
0x3e953f35,0x3f22bf7b,0xbf7f3ec4,0x3ef13f0e,0xbf620000,0x3dc93f55,0x3f46bf6d,0xbf753e48,0x3f0ebf80,0xbf7b3ec4,0x3e483f35,0x3f55bf6d,
0xbf550000,0xbe483f6d,0x3f7bbf35,0xbf0ebec4,0xbf0e3f80,0x3f7bbec4,0xbe48bf35,0xbf553f6d,0x3f550000,0x3e48bf6d,0xbf7b3f35,0x3f0e3ec4,
0x3f0ebf80,0xbf7b3ec4,0x3e483f35,0x3f55bf6d,0xbf550000,0xbe483f6d,0x3f7bbf35,0xbf0ebec4,0xbf0e3f80,0x3f7bbec4,0xbe48bf35,0xbf553f6d,
0x3f550000,0x3e48bf6d,0xbf7b3f35,0x3f0e3ec4,0xbf7f3f35,0x3e953f0e,0x3f62bf6d,0xbf22be48,0xbf460000,0xbef13f7b,0x3f75bec4,0x3dc9bf55,
0xbdc9bf35,0xbf753f55,0x3ef13ec4,0x3f46bf7b,0x3f22bf80,0xbf623e48,0xbe953f6d,0x3f7fbf0e,0x3f7fbf35,0xbe95bf0e,0xbf623f6d,0x3f223e48,
0x3f460000,0x3ef1bf7b,0xbf753ec4,0xbdc93f55,0x3dc93f35,0x3f75bf55,0xbef1bec4,0xbf463f7b,0xbf223f80,0x3f62be48,0x3e95bf6d,0xbf7f3f0e,
0xbf353f80,0x3f350000,0x3f35bf80,0xbf350000,0xbf353f80,0x3f350000,0x3f35bf80,0xbf350000,0xbf353f80,0x3f350000,0x3f35bf80,0xbf350000,
0xbf353f80,0x3f350000,0x3f35bf80,0xbf350000,0xbf353f80,0x3f350000,0x3f35bf80,0xbf350000,0xbf353f80,0x3f350000,0x3f35bf80,0xbf350000,
0xbf353f80,0x3f350000,0x3f35bf80,0xbf350000,0xbf353f80,0x3f350000,0x3f35bf80,0xbf350000,0xbf7f3f35,0xbe953f55,0x3f62bec4,0x3f22bf7b,
0xbf463f80,0x3ef13e48,0x3f75bf6d,0xbdc9bf0e,0x3dc9bf35,0xbf753f0e,0xbef13f6d,0x3f46be48,0xbf220000,0xbf623f7b,0x3e953ec4,0x3f7fbf55,
0x3f7fbf35,0x3e95bf55,0xbf623ec4,0xbf223f7b,0x3f46bf80,0xbef1be48,0xbf753f6d,0x3dc93f0e,0xbdc93f35,0x3f75bf0e,0x3ef1bf6d,0xbf463e48,
0x3f220000,0x3f62bf7b,0xbe95bec4,0xbf7f3f55,0x3f55bf80,0xbe48bec4,0xbf7b3f35,0xbf0e3f6d,0x3f0e0000,0x3f7bbf6d,0x3e48bf35,0xbf553ec4,
0xbf553f80,0x3e483ec4,0x3f7bbf35,0x3f0ebf6d,0xbf0e0000,0xbf7b3f6d,0xbe483f35,0x3f55bec4,0x3f55bf80,0xbe48bec4,0xbf7b3f35,0xbf0e3f6d,
0x3f0e0000,0x3f7bbf6d,0x3e48bf35,0xbf553ec4,0xbf553f80,0x3e483ec4,0x3f7bbf35,0x3f0ebf6d,0xbf0e0000,0xbf7b3f6d,0xbe483f35,0x3f55bec4,
0xbf753f35,0xbf463f7b,0x3dc93ec4,0x3f62bf0e,0x3ef10000,0x3f7fbf55,0x3f22bf6d,0xbe95be48,0x3e95bf35,0xbf223e48,0xbf7f3f6d,0xbef13f55,
0xbf623f80,0xbdc93f0e,0x3f46bec4,0x3f75bf7b,0x3f75bf35,0x3f46bf7b,0xbdc9bec4,0xbf623f0e,0xbef10000,0xbf7f3f55,0xbf223f6d,0x3e953e48,
0xbe953f35,0x3f22be48,0x3f7fbf6d,0x3ef1bf55,0x3f62bf80,0x3dc9bf0e,0xbf463ec4,0xbf753f7b,0xbf6d3f80,0xbec43f35,0x3ec40000,0x3f6dbf35,
0x3f6dbf80,0x3ec4bf35,0xbec40000,0xbf6d3f35,0xbf6d3f80,0xbec43f35,0x3ec40000,0x3f6dbf35,0x3f6dbf80,0x3ec4bf35,0xbec40000,0xbf6d3f35,
0xbf6d3f80,0xbec43f35,0x3ec40000,0x3f6dbf35,0x3f6dbf80,0x3ec4bf35,0xbec40000,0xbf6d3f35,0xbf6d3f80,0xbec43f35,0x3ec40000,0x3f6dbf35,
0x3f6dbf80,0x3ec4bf35,0xbec40000,0xbf6d3f35,0xbf623f35,0xbf7f3f7b,0xbf463f6d,0xbe953f0e,0x3f75bf80,0x3f22bf55,0x3dc9bec4,0xbef13e48,
0x3ef1bf35,0xbdc9be48,0xbf223ec4,0xbf753f55,0x3e950000,0x3f46bf0e,0x3f7fbf6d,0x3f62bf7b,0x3f62bf35,0x3f7fbf7b,0x3f46bf6d,0x3e95bf0e,
0xbf753f80,0xbf223f55,0xbdc93ec4,0x3ef1be48,0xbef13f35,0x3dc93e48,0x3f22bec4,0x3f75bf55,0xbe950000,0xbf463f0e,0xbf7f3f6d,0xbf623f7b,
0x3f7bbf80,0x3f55bf6d,0x3f0ebf35,0x3e48bec4,0xbe480000,0xbf0e3ec4,0xbf553f35,0xbf7b3f6d,0xbf7b3f80,0xbf553f6d,0xbf0e3f35,0xbe483ec4,
0x3e480000,0x3f0ebec4,0x3f55bf35,0x3f7bbf6d,0x3f7bbf80,0x3f55bf6d,0x3f0ebf35,0x3e48bec4,0xbe480000,0xbf0e3ec4,0xbf553f35,0xbf7b3f6d,
0xbf7b3f80,0xbf553f6d,0xbf0e3f35,0xbe483ec4,0x3e480000,0x3f0ebec4,0x3f55bf35,0x3f7bbf6d,0xbf463f35,0xbf623f55,0xbf753f6d,0xbf7f3f7b,
0xbdc90000,0xbe953e48,0xbef13ec4,0xbf223f0e,0x3f22bf35,0x3ef1bf0e,0x3e95bec4,0x3dc9be48,0x3f7fbf80,0x3f75bf7b,0x3f62bf6d,0x3f46bf55,
0x3f46bf35,0x3f62bf55,0x3f75bf6d,0x3f7fbf7b,0x3dc90000,0x3e95be48,0x3ef1bec4,0x3f22bf0e,0xbf223f35,0xbef13f0e,0xbe953ec4,0xbdc93e48,
0xbf7f3f80,0xbf753f7b,0xbf623f6d,0xbf463f55,0xbf803f80,0xbf803f80,0xbf803f80,0xbf803f80,0xbf803f80,0xbf803f80,0xbf803f80,0xbf803f80,
0xbf803f80,0xbf803f80,0xbf803f80,0xbf803f80,0xbf803f80,0xbf803f80,0xbf803f80,0xbf803f80,0xbf803f80,0xbf803f80,0xbf803f80,0xbf803f80,
0xbf803f80,0xbf803f80,0xbf803f80,0xbf803f80,0xbf803f80,0xbf803f80,0xbf803f80,0xbf803f80,0xbf803f80,0xbf803f80,0xbf803f80,0xbf803f80,
0xbf223f35,0xbef13f0e,0xbe953ec4,0xbdc93e48,0xbf7f3f80,0xbf753f7b,0xbf623f6d,0xbf463f55,0x3f46bf35,0x3f62bf55,0x3f75bf6d,0x3f7fbf7b,
0x3dc90000,0x3e95be48,0x3ef1bec4,0x3f22bf0e,0x3f22bf35,0x3ef1bf0e,0x3e95bec4,0x3dc9be48,0x3f7fbf80,0x3f75bf7b,0x3f62bf6d,0x3f46bf55,
0xbf463f35,0xbf623f55,0xbf753f6d,0xbf7f3f7b,0xbdc90000,0xbe953e48,0xbef13ec4,0xbf223f0e,0x3f7bbf80,0x3f55bf6d,0x3f0ebf35,0x3e48bec4,
0xbe480000,0xbf0e3ec4,0xbf553f35,0xbf7b3f6d,0xbf7b3f80,0xbf553f6d,0xbf0e3f35,0xbe483ec4,0x3e480000,0x3f0ebec4,0x3f55bf35,0x3f7bbf6d,
0x3f7bbf80,0x3f55bf6d,0x3f0ebf35,0x3e48bec4,0xbe480000,0xbf0e3ec4,0xbf553f35,0xbf7b3f6d,0xbf7b3f80,0xbf553f6d,0xbf0e3f35,0xbe483ec4,
0x3e480000,0x3f0ebec4,0x3f55bf35,0x3f7bbf6d,0xbef13f35,0x3dc93e48,0x3f22bec4,0x3f75bf55,0xbe950000,0xbf463f0e,0xbf7f3f6d,0xbf623f7b,
0x3f62bf35,0x3f7fbf7b,0x3f46bf6d,0x3e95bf0e,0xbf753f80,0xbf223f55,0xbdc93ec4,0x3ef1be48,0x3ef1bf35,0xbdc9be48,0xbf223ec4,0xbf753f55,
0x3e950000,0x3f46bf0e,0x3f7fbf6d,0x3f62bf7b,0xbf623f35,0xbf7f3f7b,0xbf463f6d,0xbe953f0e,0x3f75bf80,0x3f22bf55,0x3dc9bec4,0xbef13e48,
0xbf6d3f80,0xbec43f35,0x3ec40000,0x3f6dbf35,0x3f6dbf80,0x3ec4bf35,0xbec40000,0xbf6d3f35,0xbf6d3f80,0xbec43f35,0x3ec40000,0x3f6dbf35,
0x3f6dbf80,0x3ec4bf35,0xbec40000,0xbf6d3f35,0xbf6d3f80,0xbec43f35,0x3ec40000,0x3f6dbf35,0x3f6dbf80,0x3ec4bf35,0xbec40000,0xbf6d3f35,
0xbf6d3f80,0xbec43f35,0x3ec40000,0x3f6dbf35,0x3f6dbf80,0x3ec4bf35,0xbec40000,0xbf6d3f35,0xbe953f35,0x3f22be48,0x3f7fbf6d,0x3ef1bf55,
0x3f62bf80,0x3dc9bf0e,0xbf463ec4,0xbf753f7b,0x3f75bf35,0x3f46bf7b,0xbdc9bec4,0xbf623f0e,0xbef10000,0xbf7f3f55,0xbf223f6d,0x3e953e48,
0x3e95bf35,0xbf223e48,0xbf7f3f6d,0xbef13f55,0xbf623f80,0xbdc93f0e,0x3f46bec4,0x3f75bf7b,0xbf753f35,0xbf463f7b,0x3dc93ec4,0x3f62bf0e,
0x3ef10000,0x3f7fbf55,0x3f22bf6d,0xbe95be48,0x3f55bf80,0xbe48bec4,0xbf7b3f35,0xbf0e3f6d,0x3f0e0000,0x3f7bbf6d,0x3e48bf35,0xbf553ec4,
0xbf553f80,0x3e483ec4,0x3f7bbf35,0x3f0ebf6d,0xbf0e0000,0xbf7b3f6d,0xbe483f35,0x3f55bec4,0x3f55bf80,0xbe48bec4,0xbf7b3f35,0xbf0e3f6d,
0x3f0e0000,0x3f7bbf6d,0x3e48bf35,0xbf553ec4,0xbf553f80,0x3e483ec4,0x3f7bbf35,0x3f0ebf6d,0xbf0e0000,0xbf7b3f6d,0xbe483f35,0x3f55bec4,
0xbdc93f35,0x3f75bf0e,0x3ef1bf6d,0xbf463e48,0x3f220000,0x3f62bf7b,0xbe95bec4,0xbf7f3f55,0x3f7fbf35,0x3e95bf55,0xbf623ec4,0xbf223f7b,
0x3f46bf80,0xbef1be48,0xbf753f6d,0x3dc93f0e,0x3dc9bf35,0xbf753f0e,0xbef13f6d,0x3f46be48,0xbf220000,0xbf623f7b,0x3e953ec4,0x3f7fbf55,
0xbf7f3f35,0xbe953f55,0x3f62bec4,0x3f22bf7b,0xbf463f80,0x3ef13e48,0x3f75bf6d,0xbdc9bf0e,0xbf353f80,0x3f350000,0x3f35bf80,0xbf350000,
0xbf353f80,0x3f350000,0x3f35bf80,0xbf350000,0xbf353f80,0x3f350000,0x3f35bf80,0xbf350000,0xbf353f80,0x3f350000,0x3f35bf80,0xbf350000,
0xbf353f80,0x3f350000,0x3f35bf80,0xbf350000,0xbf353f80,0x3f350000,0x3f35bf80,0xbf350000,0xbf353f80,0x3f350000,0x3f35bf80,0xbf350000,
0xbf353f80,0x3f350000,0x3f35bf80,0xbf350000,0x3dc93f35,0x3f75bf55,0xbef1bec4,0xbf463f7b,0xbf223f80,0x3f62be48,0x3e95bf6d,0xbf7f3f0e,
0x3f7fbf35,0xbe95bf0e,0xbf623f6d,0x3f223e48,0x3f460000,0x3ef1bf7b,0xbf753ec4,0xbdc93f55,0xbdc9bf35,0xbf753f55,0x3ef13ec4,0x3f46bf7b,
0x3f22bf80,0xbf623e48,0xbe953f6d,0x3f7fbf0e,0xbf7f3f35,0x3e953f0e,0x3f62bf6d,0xbf22be48,0xbf460000,0xbef13f7b,0x3f75bec4,0x3dc9bf55,
0x3f0ebf80,0xbf7b3ec4,0x3e483f35,0x3f55bf6d,0xbf550000,0xbe483f6d,0x3f7bbf35,0xbf0ebec4,0xbf0e3f80,0x3f7bbec4,0xbe48bf35,0xbf553f6d,
0x3f550000,0x3e48bf6d,0xbf7b3f35,0x3f0e3ec4,0x3f0ebf80,0xbf7b3ec4,0x3e483f35,0x3f55bf6d,0xbf550000,0xbe483f6d,0x3f7bbf35,0xbf0ebec4,
0xbf0e3f80,0x3f7bbec4,0xbe48bf35,0xbf553f6d,0x3f550000,0x3e48bf6d,0xbf7b3f35,0x3f0e3ec4,0x3e953f35,0x3f22bf7b,0xbf7f3ec4,0x3ef13f0e,
0xbf620000,0x3dc93f55,0x3f46bf6d,0xbf753e48,0x3f75bf35,0xbf46be48,0xbdc93f6d,0x3f62bf55,0xbef13f80,0x3f7fbf0e,0xbf22bec4,0xbe953f7b,
0xbe95bf35,0xbf223f7b,0x3f7fbec4,0xbef1bf0e,0x3f620000,0xbdc9bf55,0xbf463f6d,0x3f75be48,0xbf753f35,0x3f463e48,0x3dc9bf6d,0xbf623f55,
0x3ef1bf80,0xbf7f3f0e,0x3f223ec4,0x3e95bf7b,0xbec43f80,0x3f6dbf35,0xbf6d0000,0x3ec43f35,0x3ec4bf80,0xbf6d3f35,0x3f6d0000,0xbec4bf35,
0xbec43f80,0x3f6dbf35,0xbf6d0000,0x3ec43f35,0x3ec4bf80,0xbf6d3f35,0x3f6d0000,0xbec4bf35,0xbec43f80,0x3f6dbf35,0xbf6d0000,0x3ec43f35,
0x3ec4bf80,0xbf6d3f35,0x3f6d0000,0xbec4bf35,0xbec43f80,0x3f6dbf35,0xbf6d0000,0x3ec43f35,0x3ec4bf80,0xbf6d3f35,0x3f6d0000,0xbec4bf35,
0x3ef13f35,0x3dc9bf7b,0xbf223f6d,0x3f75bf0e,0x3e95bf80,0xbf463f55,0x3f7fbec4,0xbf62be48,0x3f62bf35,0xbf7f3e48,0x3f463ec4,0xbe95bf55,
0xbf750000,0x3f223f0e,0xbdc9bf6d,0xbef13f7b,0xbef1bf35,0xbdc93f7b,0x3f22bf6d,0xbf753f0e,0xbe953f80,0x3f46bf55,0xbf7f3ec4,0x3f623e48,
0xbf623f35,0x3f7fbe48,0xbf46bec4,0x3e953f55,0x3f750000,0xbf22bf0e,0x3dc93f6d,0x3ef1bf7b,0x3e48bf80,0xbf0e3f6d,0x3f55bf35,0xbf7b3ec4,
0x3f7b0000,0xbf55bec4,0x3f0e3f35,0xbe48bf6d,0xbe483f80,0x3f0ebf6d,0xbf553f35,0x3f7bbec4,0xbf7b0000,0x3f553ec4,0xbf0ebf35,0x3e483f6d,
0x3e48bf80,0xbf0e3f6d,0x3f55bf35,0xbf7b3ec4,0x3f7b0000,0xbf55bec4,0x3f0e3f35,0xbe48bf6d,0xbe483f80,0x3f0ebf6d,0xbf553f35,0x3f7bbec4,
0xbf7b0000,0x3f553ec4,0xbf0ebf35,0x3e483f6d,0x3f223f35,0xbef1bf55,0x3e953f6d,0xbdc9bf7b,0x3f7f0000,0xbf75be48,0x3f623ec4,0xbf46bf0e,
0x3f46bf35,0xbf623f0e,0x3f75bec4,0xbf7f3e48,0x3dc9bf80,0xbe953f7b,0x3ef1bf6d,0xbf223f55,0xbf22bf35,0x3ef13f55,0xbe95bf6d,0x3dc93f7b,
0xbf7f0000,0x3f753e48,0xbf62bec4,0x3f463f0e,0xbf463f35,0x3f62bf0e,0xbf753ec4,0x3f7fbe48,0xbdc93f80,0x3e95bf7b,0xbef13f6d,0x3f22bf55,
0x3f80,0xbf80,0x3f80,0xbf80,0x3f80,0xbf80,0x3f80,0xbf80,0x3f80,0xbf80,0x3f80,0xbf80,
0x3f80,0xbf80,0x3f80,0xbf80,0x3f80,0xbf80,0x3f80,0xbf80,0x3f80,0xbf80,0x3f80,0xbf80,
0x3f80,0xbf80,0x3f80,0xbf80,0x3f80,0xbf80,0x3f80,0xbf80,0x3f463f35,0xbf62bf0e,0x3f753ec4,0xbf7fbe48,
0x3dc93f80,0xbe95bf7b,0x3ef13f6d,0xbf22bf55,0x3f22bf35,0xbef13f55,0x3e95bf6d,0xbdc93f7b,0x3f7f0000,0xbf753e48,0x3f62bec4,0xbf463f0e,
0xbf46bf35,0x3f623f0e,0xbf75bec4,0x3f7f3e48,0xbdc9bf80,0x3e953f7b,0xbef1bf6d,0x3f223f55,0xbf223f35,0x3ef1bf55,0xbe953f6d,0x3dc9bf7b,
0xbf7f0000,0x3f75be48,0xbf623ec4,0x3f46bf0e,0xbe48bf80,0x3f0e3f6d,0xbf55bf35,0x3f7b3ec4,0xbf7b0000,0x3f55bec4,0xbf0e3f35,0x3e48bf6d,
0x3e483f80,0xbf0ebf6d,0x3f553f35,0xbf7bbec4,0x3f7b0000,0xbf553ec4,0x3f0ebf35,0xbe483f6d,0xbe48bf80,0x3f0e3f6d,0xbf55bf35,0x3f7b3ec4,
0xbf7b0000,0x3f55bec4,0xbf0e3f35,0x3e48bf6d,0x3e483f80,0xbf0ebf6d,0x3f553f35,0xbf7bbec4,0x3f7b0000,0xbf553ec4,0x3f0ebf35,0xbe483f6d,
0x3f623f35,0xbf7fbe48,0x3f46bec4,0xbe953f55,0xbf750000,0x3f22bf0e,0xbdc93f6d,0xbef1bf7b,0x3ef1bf35,0x3dc93f7b,0xbf22bf6d,0x3f753f0e,
0x3e953f80,0xbf46bf55,0x3f7f3ec4,0xbf623e48,0xbf62bf35,0x3f7f3e48,0xbf463ec4,0x3e95bf55,0x3f750000,0xbf223f0e,0x3dc9bf6d,0x3ef13f7b,
0xbef13f35,0xbdc9bf7b,0x3f223f6d,0xbf75bf0e,0xbe95bf80,0x3f463f55,0xbf7fbec4,0x3f62be48,0x3ec43f80,0xbf6dbf35,0x3f6d0000,0xbec43f35,
0xbec4bf80,0x3f6d3f35,0xbf6d0000,0x3ec4bf35,0x3ec43f80,0xbf6dbf35,0x3f6d0000,0xbec43f35,0xbec4bf80,0x3f6d3f35,0xbf6d0000,0x3ec4bf35,
0x3ec43f80,0xbf6dbf35,0x3f6d0000,0xbec43f35,0xbec4bf80,0x3f6d3f35,0xbf6d0000,0x3ec4bf35,0x3ec43f80,0xbf6dbf35,0x3f6d0000,0xbec43f35,
0xbec4bf80,0x3f6d3f35,0xbf6d0000,0x3ec4bf35,0x3f753f35,0xbf463e48,0xbdc9bf6d,0x3f623f55,0xbef1bf80,0x3f7f3f0e,0xbf223ec4,0xbe95bf7b,
0x3e95bf35,0x3f223f7b,0xbf7fbec4,0x3ef1bf0e,0xbf620000,0x3dc9bf55,0x3f463f6d,0xbf75be48,0xbf75bf35,0x3f46be48,0x3dc93f6d,0xbf62bf55,
0x3ef13f80,0xbf7fbf0e,0x3f22bec4,0x3e953f7b,0xbe953f35,0xbf22bf7b,0x3f7f3ec4,0xbef13f0e,0x3f620000,0xbdc93f55,0xbf46bf6d,0x3f753e48,
0xbf0ebf80,0x3f7b3ec4,0xbe483f35,0xbf55bf6d,0x3f550000,0x3e483f6d,0xbf7bbf35,0x3f0ebec4,0x3f0e3f80,0xbf7bbec4,0x3e48bf35,0x3f553f6d,
0xbf550000,0xbe48bf6d,0x3f7b3f35,0xbf0e3ec4,0xbf0ebf80,0x3f7b3ec4,0xbe483f35,0xbf55bf6d,0x3f550000,0x3e483f6d,0xbf7bbf35,0x3f0ebec4,
0x3f0e3f80,0xbf7bbec4,0x3e48bf35,0x3f553f6d,0xbf550000,0xbe48bf6d,0x3f7b3f35,0xbf0e3ec4,0x3f7f3f35,0xbe953f0e,0xbf62bf6d,0x3f22be48,
0x3f460000,0x3ef13f7b,0xbf75bec4,0xbdc9bf55,0x3dc9bf35,0x3f753f55,0xbef13ec4,0xbf46bf7b,0xbf22bf80,0x3f623e48,0x3e953f6d,0xbf7fbf0e,
0xbf7fbf35,0x3e95bf0e,0x3f623f6d,0xbf223e48,0xbf460000,0xbef1bf7b,0x3f753ec4,0x3dc93f55,0xbdc93f35,0xbf75bf55,0x3ef1bec4,0x3f463f7b,
0x3f223f80,0xbf62be48,0xbe95bf6d,0x3f7f3f0e,0x3f353f80,0xbf350000,0xbf35bf80,0x3f350000,0x3f353f80,0xbf350000,0xbf35bf80,0x3f350000,
0x3f353f80,0xbf350000,0xbf35bf80,0x3f350000,0x3f353f80,0xbf350000,0xbf35bf80,0x3f350000,0x3f353f80,0xbf350000,0xbf35bf80,0x3f350000,
0x3f353f80,0xbf350000,0xbf35bf80,0x3f350000,0x3f353f80,0xbf350000,0xbf35bf80,0x3f350000,0x3f353f80,0xbf350000,0xbf35bf80,0x3f350000,
0x3f7f3f35,0x3e953f55,0xbf62bec4,0xbf22bf7b,0x3f463f80,0xbef13e48,0xbf75bf6d,0x3dc9bf0e,0xbdc9bf35,0x3f753f0e,0x3ef13f6d,0xbf46be48,
0x3f220000,0x3f623f7b,0xbe953ec4,0xbf7fbf55,0xbf7fbf35,0xbe95bf55,0x3f623ec4,0x3f223f7b,0xbf46bf80,0x3ef1be48,0x3f753f6d,0xbdc93f0e,
0x3dc93f35,0xbf75bf0e,0xbef1bf6d,0x3f463e48,0xbf220000,0xbf62bf7b,0x3e95bec4,0x3f7f3f55,0xbf55bf80,0x3e48bec4,0x3f7b3f35,0x3f0e3f6d,
0xbf0e0000,0xbf7bbf6d,0xbe48bf35,0x3f553ec4,0x3f553f80,0xbe483ec4,0xbf7bbf35,0xbf0ebf6d,0x3f0e0000,0x3f7b3f6d,0x3e483f35,0xbf55bec4,
0xbf55bf80,0x3e48bec4,0x3f7b3f35,0x3f0e3f6d,0xbf0e0000,0xbf7bbf6d,0xbe48bf35,0x3f553ec4,0x3f553f80,0xbe483ec4,0xbf7bbf35,0xbf0ebf6d,
0x3f0e0000,0x3f7b3f6d,0x3e483f35,0xbf55bec4,0x3f753f35,0x3f463f7b,0xbdc93ec4,0xbf62bf0e,0xbef10000,0xbf7fbf55,0xbf22bf6d,0x3e95be48,
0xbe95bf35,0x3f223e48,0x3f7f3f6d,0x3ef13f55,0x3f623f80,0x3dc93f0e,0xbf46bec4,0xbf75bf7b,0xbf75bf35,0xbf46bf7b,0x3dc9bec4,0x3f623f0e,
0x3ef10000,0x3f7f3f55,0x3f223f6d,0xbe953e48,0x3e953f35,0xbf22be48,0xbf7fbf6d,0xbef1bf55,0xbf62bf80,0xbdc9bf0e,0x3f463ec4,0x3f753f7b,
0x3f6d3f80,0x3ec43f35,0xbec40000,0xbf6dbf35,0xbf6dbf80,0xbec4bf35,0x3ec40000,0x3f6d3f35,0x3f6d3f80,0x3ec43f35,0xbec40000,0xbf6dbf35,
0xbf6dbf80,0xbec4bf35,0x3ec40000,0x3f6d3f35,0x3f6d3f80,0x3ec43f35,0xbec40000,0xbf6dbf35,0xbf6dbf80,0xbec4bf35,0x3ec40000,0x3f6d3f35,
0x3f6d3f80,0x3ec43f35,0xbec40000,0xbf6dbf35,0xbf6dbf80,0xbec4bf35,0x3ec40000,0x3f6d3f35,0x3f623f35,0x3f7f3f7b,0x3f463f6d,0x3e953f0e,
0xbf75bf80,0xbf22bf55,0xbdc9bec4,0x3ef13e48,0xbef1bf35,0x3dc9be48,0x3f223ec4,0x3f753f55,0xbe950000,0xbf46bf0e,0xbf7fbf6d,0xbf62bf7b,
0xbf62bf35,0xbf7fbf7b,0xbf46bf6d,0xbe95bf0e,0x3f753f80,0x3f223f55,0x3dc93ec4,0xbef1be48,0x3ef13f35,0xbdc93e48,0xbf22bec4,0xbf75bf55,
0x3e950000,0x3f463f0e,0x3f7f3f6d,0x3f623f7b,0xbf7bbf80,0xbf55bf6d,0xbf0ebf35,0xbe48bec4,0x3e480000,0x3f0e3ec4,0x3f553f35,0x3f7b3f6d,
0x3f7b3f80,0x3f553f6d,0x3f0e3f35,0x3e483ec4,0xbe480000,0xbf0ebec4,0xbf55bf35,0xbf7bbf6d,0xbf7bbf80,0xbf55bf6d,0xbf0ebf35,0xbe48bec4,
0x3e480000,0x3f0e3ec4,0x3f553f35,0x3f7b3f6d,0x3f7b3f80,0x3f553f6d,0x3f0e3f35,0x3e483ec4,0xbe480000,0xbf0ebec4,0xbf55bf35,0xbf7bbf6d,
0x3f463f35,0x3f623f55,0x3f753f6d,0x3f7f3f7b,0x3dc90000,0x3e953e48,0x3ef13ec4,0x3f223f0e,0xbf22bf35,0xbef1bf0e,0xbe95bec4,0xbdc9be48,
0xbf7fbf80,0xbf75bf7b,0xbf62bf6d,0xbf46bf55,0xbf46bf35,0xbf62bf55,0xbf75bf6d,0xbf7fbf7b,0xbdc90000,0xbe95be48,0xbef1bec4,0xbf22bf0e,
0x3f223f35,0x3ef13f0e,0x3e953ec4,0x3dc93e48,0x3f7f3f80,0x3f753f7b,0x3f623f6d,0x3f463f55,0x0,0x0,0x0,0x0,
0x0,0x0,0x0,0x0,0x0,0x0,0x0,0x0,0x0,0x0,0x0,0x0,
0x0,0x0,0x0,0x0,0x0,0x0,0x0,0x0,0x0,0x0,0x0,0x0,
0x0,0x0,0x0,0x0,0x3f463f35,0x3f623f55,0x3f753f6d,0x3f7f3f7b,0x3dc90000,0x3e953e48,0x3ef13ec4,0x3f223f0e,
0x3f223f35,0x3ef13f0e,0x3e953ec4,0x3dc93e48,0x3f7f3f80,0x3f753f7b,0x3f623f6d,0x3f463f55,0xbf46bf35,0xbf62bf55,0xbf75bf6d,0xbf7fbf7b,
0xbdc90000,0xbe95be48,0xbef1bec4,0xbf22bf0e,0xbf22bf35,0xbef1bf0e,0xbe95bec4,0xbdc9be48,0xbf7fbf80,0xbf75bf7b,0xbf62bf6d,0xbf46bf55,
0xbe480000,0xbf0ebec4,0xbf55bf35,0xbf7bbf6d,0xbf7bbf80,0xbf55bf6d,0xbf0ebf35,0xbe48bec4,0x3e480000,0x3f0e3ec4,0x3f553f35,0x3f7b3f6d,
0x3f7b3f80,0x3f553f6d,0x3f0e3f35,0x3e483ec4,0xbe480000,0xbf0ebec4,0xbf55bf35,0xbf7bbf6d,0xbf7bbf80,0xbf55bf6d,0xbf0ebf35,0xbe48bec4,
0x3e480000,0x3f0e3ec4,0x3f553f35,0x3f7b3f6d,0x3f7b3f80,0x3f553f6d,0x3f0e3f35,0x3e483ec4,0x3f623f35,0x3f7f3f7b,0x3f463f6d,0x3e953f0e,
0xbf75bf80,0xbf22bf55,0xbdc9bec4,0x3ef13e48,0x3ef13f35,0xbdc93e48,0xbf22bec4,0xbf75bf55,0x3e950000,0x3f463f0e,0x3f7f3f6d,0x3f623f7b,
0xbf62bf35,0xbf7fbf7b,0xbf46bf6d,0xbe95bf0e,0x3f753f80,0x3f223f55,0x3dc93ec4,0xbef1be48,0xbef1bf35,0x3dc9be48,0x3f223ec4,0x3f753f55,
0xbe950000,0xbf46bf0e,0xbf7fbf6d,0xbf62bf7b,0x3ec40000,0x3f6d3f35,0x3f6d3f80,0x3ec43f35,0xbec40000,0xbf6dbf35,0xbf6dbf80,0xbec4bf35,
0x3ec40000,0x3f6d3f35,0x3f6d3f80,0x3ec43f35,0xbec40000,0xbf6dbf35,0xbf6dbf80,0xbec4bf35,0x3ec40000,0x3f6d3f35,0x3f6d3f80,0x3ec43f35,
0xbec40000,0xbf6dbf35,0xbf6dbf80,0xbec4bf35,0x3ec40000,0x3f6d3f35,0x3f6d3f80,0x3ec43f35,0xbec40000,0xbf6dbf35,0xbf6dbf80,0xbec4bf35,
0x3f753f35,0x3f463f7b,0xbdc93ec4,0xbf62bf0e,0xbef10000,0xbf7fbf55,0xbf22bf6d,0x3e95be48,0x3e953f35,0xbf22be48,0xbf7fbf6d,0xbef1bf55,
0xbf62bf80,0xbdc9bf0e,0x3f463ec4,0x3f753f7b,0xbf75bf35,0xbf46bf7b,0x3dc9bec4,0x3f623f0e,0x3ef10000,0x3f7f3f55,0x3f223f6d,0xbe953e48,
0xbe95bf35,0x3f223e48,0x3f7f3f6d,0x3ef13f55,0x3f623f80,0x3dc93f0e,0xbf46bec4,0xbf75bf7b,0xbf0e0000,0xbf7bbf6d,0xbe48bf35,0x3f553ec4,
0x3f553f80,0xbe483ec4,0xbf7bbf35,0xbf0ebf6d,0x3f0e0000,0x3f7b3f6d,0x3e483f35,0xbf55bec4,0xbf55bf80,0x3e48bec4,0x3f7b3f35,0x3f0e3f6d,
0xbf0e0000,0xbf7bbf6d,0xbe48bf35,0x3f553ec4,0x3f553f80,0xbe483ec4,0xbf7bbf35,0xbf0ebf6d,0x3f0e0000,0x3f7b3f6d,0x3e483f35,0xbf55bec4,
0xbf55bf80,0x3e48bec4,0x3f7b3f35,0x3f0e3f6d,0x3f7f3f35,0x3e953f55,0xbf62bec4,0xbf22bf7b,0x3f463f80,0xbef13e48,0xbf75bf6d,0x3dc9bf0e,
0x3dc93f35,0xbf75bf0e,0xbef1bf6d,0x3f463e48,0xbf220000,0xbf62bf7b,0x3e95bec4,0x3f7f3f55,0xbf7fbf35,0xbe95bf55,0x3f623ec4,0x3f223f7b,
0xbf46bf80,0x3ef1be48,0x3f753f6d,0xbdc93f0e,0xbdc9bf35,0x3f753f0e,0x3ef13f6d,0xbf46be48,0x3f220000,0x3f623f7b,0xbe953ec4,0xbf7fbf55,
0x3f350000,0x3f353f80,0xbf350000,0xbf35bf80,0x3f350000,0x3f353f80,0xbf350000,0xbf35bf80,0x3f350000,0x3f353f80,0xbf350000,0xbf35bf80,
0x3f350000,0x3f353f80,0xbf350000,0xbf35bf80,0x3f350000,0x3f353f80,0xbf350000,0xbf35bf80,0x3f350000,0x3f353f80,0xbf350000,0xbf35bf80,
0x3f350000,0x3f353f80,0xbf350000,0xbf35bf80,0x3f350000,0x3f353f80,0xbf350000,0xbf35bf80,0x3f7f3f35,0xbe953f0e,0xbf62bf6d,0x3f22be48,
0x3f460000,0x3ef13f7b,0xbf75bec4,0xbdc9bf55,0xbdc93f35,0xbf75bf55,0x3ef1bec4,0x3f463f7b,0x3f223f80,0xbf62be48,0xbe95bf6d,0x3f7f3f0e,
0xbf7fbf35,0x3e95bf0e,0x3f623f6d,0xbf223e48,0xbf460000,0xbef1bf7b,0x3f753ec4,0x3dc93f55,0x3dc9bf35,0x3f753f55,0xbef13ec4,0xbf46bf7b,
0xbf22bf80,0x3f623e48,0x3e953f6d,0xbf7fbf0e,0xbf550000,0xbe48bf6d,0x3f7b3f35,0xbf0e3ec4,0xbf0ebf80,0x3f7b3ec4,0xbe483f35,0xbf55bf6d,
0x3f550000,0x3e483f6d,0xbf7bbf35,0x3f0ebec4,0x3f0e3f80,0xbf7bbec4,0x3e48bf35,0x3f553f6d,0xbf550000,0xbe48bf6d,0x3f7b3f35,0xbf0e3ec4,
0xbf0ebf80,0x3f7b3ec4,0xbe483f35,0xbf55bf6d,0x3f550000,0x3e483f6d,0xbf7bbf35,0x3f0ebec4,0x3f0e3f80,0xbf7bbec4,0x3e48bf35,0x3f553f6d,
0x3f753f35,0xbf463e48,0xbdc9bf6d,0x3f623f55,0xbef1bf80,0x3f7f3f0e,0xbf223ec4,0xbe95bf7b,0xbe953f35,0xbf22bf7b,0x3f7f3ec4,0xbef13f0e,
0x3f620000,0xbdc93f55,0xbf46bf6d,0x3f753e48,0xbf75bf35,0x3f46be48,0x3dc93f6d,0xbf62bf55,0x3ef13f80,0xbf7fbf0e,0x3f22bec4,0x3e953f7b,
0x3e95bf35,0x3f223f7b,0xbf7fbec4,0x3ef1bf0e,0xbf620000,0x3dc9bf55,0x3f463f6d,0xbf75be48,0x3f6d0000,0xbec43f35,0xbec4bf80,0x3f6d3f35,
0xbf6d0000,0x3ec4bf35,0x3ec43f80,0xbf6dbf35,0x3f6d0000,0xbec43f35,0xbec4bf80,0x3f6d3f35,0xbf6d0000,0x3ec4bf35,0x3ec43f80,0xbf6dbf35,
0x3f6d0000,0xbec43f35,0xbec4bf80,0x3f6d3f35,0xbf6d0000,0x3ec4bf35,0x3ec43f80,0xbf6dbf35,0x3f6d0000,0xbec43f35,0xbec4bf80,0x3f6d3f35,
0xbf6d0000,0x3ec4bf35,0x3ec43f80,0xbf6dbf35,0x3f623f35,0xbf7fbe48,0x3f46bec4,0xbe953f55,0xbf750000,0x3f22bf0e,0xbdc93f6d,0xbef1bf7b,
0xbef13f35,0xbdc9bf7b,0x3f223f6d,0xbf75bf0e,0xbe95bf80,0x3f463f55,0xbf7fbec4,0x3f62be48,0xbf62bf35,0x3f7f3e48,0xbf463ec4,0x3e95bf55,
0x3f750000,0xbf223f0e,0x3dc9bf6d,0x3ef13f7b,0x3ef1bf35,0x3dc93f7b,0xbf22bf6d,0x3f753f0e,0x3e953f80,0xbf46bf55,0x3f7f3ec4,0xbf623e48,
0xbf7b0000,0x3f55bec4,0xbf0e3f35,0x3e48bf6d,0x3e483f80,0xbf0ebf6d,0x3f553f35,0xbf7bbec4,0x3f7b0000,0xbf553ec4,0x3f0ebf35,0xbe483f6d,
0xbe48bf80,0x3f0e3f6d,0xbf55bf35,0x3f7b3ec4,0xbf7b0000,0x3f55bec4,0xbf0e3f35,0x3e48bf6d,0x3e483f80,0xbf0ebf6d,0x3f553f35,0xbf7bbec4,
0x3f7b0000,0xbf553ec4,0x3f0ebf35,0xbe483f6d,0xbe48bf80,0x3f0e3f6d,0xbf55bf35,0x3f7b3ec4,0x3f463f35,0xbf62bf0e,0x3f753ec4,0xbf7fbe48,
0x3dc93f80,0xbe95bf7b,0x3ef13f6d,0xbf22bf55,0xbf223f35,0x3ef1bf55,0xbe953f6d,0x3dc9bf7b,0xbf7f0000,0x3f75be48,0xbf623ec4,0x3f46bf0e,
0xbf46bf35,0x3f623f0e,0xbf75bec4,0x3f7f3e48,0xbdc9bf80,0x3e953f7b,0xbef1bf6d,0x3f223f55,0x3f22bf35,0xbef13f55,0x3e95bf6d,0xbdc93f7b,
0x3f7f0000,0xbf753e48,0x3f62bec4,0xbf463f0e,0x3f800000,0xbf800000,0x3f800000,0xbf800000,0x3f800000,0xbf800000,0x3f800000,0xbf800000,
0x3f800000,0xbf800000,0x3f800000,0xbf800000,0x3f800000,0xbf800000,0x3f800000,0xbf800000,0x3f800000,0xbf800000,0x3f800000,0xbf800000,
0x3f800000,0xbf800000,0x3f800000,0xbf800000,0x3f800000,0xbf800000,0x3f800000,0xbf800000,0x3f800000,0xbf800000,0x3f800000,0xbf800000,
0x3f223f35,0xbef1bf55,0x3e953f6d,0xbdc9bf7b,0x3f7f0000,0xbf75be48,0x3f623ec4,0xbf46bf0e,0xbf463f35,0x3f62bf0e,0xbf753ec4,0x3f7fbe48,
0xbdc93f80,0x3e95bf7b,0xbef13f6d,0x3f22bf55,0xbf22bf35,0x3ef13f55,0xbe95bf6d,0x3dc93f7b,0xbf7f0000,0x3f753e48,0xbf62bec4,0x3f463f0e,
0x3f46bf35,0xbf623f0e,0x3f75bec4,0xbf7f3e48,0x3dc9bf80,0xbe953f7b,0x3ef1bf6d,0xbf223f55,0xbf7b0000,0x3f553ec4,0xbf0ebf35,0x3e483f6d,
0x3e48bf80,0xbf0e3f6d,0x3f55bf35,0xbf7b3ec4,0x3f7b0000,0xbf55bec4,0x3f0e3f35,0xbe48bf6d,0xbe483f80,0x3f0ebf6d,0xbf553f35,0x3f7bbec4,
0xbf7b0000,0x3f553ec4,0xbf0ebf35,0x3e483f6d,0x3e48bf80,0xbf0e3f6d,0x3f55bf35,0xbf7b3ec4,0x3f7b0000,0xbf55bec4,0x3f0e3f35,0xbe48bf6d,
0xbe483f80,0x3f0ebf6d,0xbf553f35,0x3f7bbec4,0x3ef13f35,0x3dc9bf7b,0xbf223f6d,0x3f75bf0e,0x3e95bf80,0xbf463f55,0x3f7fbec4,0xbf62be48,
0xbf623f35,0x3f7fbe48,0xbf46bec4,0x3e953f55,0x3f750000,0xbf22bf0e,0x3dc93f6d,0x3ef1bf7b,0xbef1bf35,0xbdc93f7b,0x3f22bf6d,0xbf753f0e,
0xbe953f80,0x3f46bf55,0xbf7f3ec4,0x3f623e48,0x3f62bf35,0xbf7f3e48,0x3f463ec4,0xbe95bf55,0xbf750000,0x3f223f0e,0xbdc9bf6d,0xbef13f7b,
0x3f6d0000,0xbec4bf35,0xbec43f80,0x3f6dbf35,0xbf6d0000,0x3ec43f35,0x3ec4bf80,0xbf6d3f35,0x3f6d0000,0xbec4bf35,0xbec43f80,0x3f6dbf35,
0xbf6d0000,0x3ec43f35,0x3ec4bf80,0xbf6d3f35,0x3f6d0000,0xbec4bf35,0xbec43f80,0x3f6dbf35,0xbf6d0000,0x3ec43f35,0x3ec4bf80,0xbf6d3f35,
0x3f6d0000,0xbec4bf35,0xbec43f80,0x3f6dbf35,0xbf6d0000,0x3ec43f35,0x3ec4bf80,0xbf6d3f35,0x3e953f35,0x3f22bf7b,0xbf7f3ec4,0x3ef13f0e,
0xbf620000,0x3dc93f55,0x3f46bf6d,0xbf753e48,0xbf753f35,0x3f463e48,0x3dc9bf6d,0xbf623f55,0x3ef1bf80,0xbf7f3f0e,0x3f223ec4,0x3e95bf7b,
0xbe95bf35,0xbf223f7b,0x3f7fbec4,0xbef1bf0e,0x3f620000,0xbdc9bf55,0xbf463f6d,0x3f75be48,0x3f75bf35,0xbf46be48,0xbdc93f6d,0x3f62bf55,
0xbef13f80,0x3f7fbf0e,0xbf22bec4,0xbe953f7b,0xbf550000,0xbe483f6d,0x3f7bbf35,0xbf0ebec4,0xbf0e3f80,0x3f7bbec4,0xbe48bf35,0xbf553f6d,
0x3f550000,0x3e48bf6d,0xbf7b3f35,0x3f0e3ec4,0x3f0ebf80,0xbf7b3ec4,0x3e483f35,0x3f55bf6d,0xbf550000,0xbe483f6d,0x3f7bbf35,0xbf0ebec4,
0xbf0e3f80,0x3f7bbec4,0xbe48bf35,0xbf553f6d,0x3f550000,0x3e48bf6d,0xbf7b3f35,0x3f0e3ec4,0x3f0ebf80,0xbf7b3ec4,0x3e483f35,0x3f55bf6d,
0x3dc93f35,0x3f75bf55,0xbef1bec4,0xbf463f7b,0xbf223f80,0x3f62be48,0x3e95bf6d,0xbf7f3f0e,0xbf7f3f35,0x3e953f0e,0x3f62bf6d,0xbf22be48,
0xbf460000,0xbef13f7b,0x3f75bec4,0x3dc9bf55,0xbdc9bf35,0xbf753f55,0x3ef13ec4,0x3f46bf7b,0x3f22bf80,0xbf623e48,0xbe953f6d,0x3f7fbf0e,
0x3f7fbf35,0xbe95bf0e,0xbf623f6d,0x3f223e48,0x3f460000,0x3ef1bf7b,0xbf753ec4,0xbdc93f55,0x3f350000,0x3f35bf80,0xbf350000,0xbf353f80,
0x3f350000,0x3f35bf80,0xbf350000,0xbf353f80,0x3f350000,0x3f35bf80,0xbf350000,0xbf353f80,0x3f350000,0x3f35bf80,0xbf350000,0xbf353f80,
0x3f350000,0x3f35bf80,0xbf350000,0xbf353f80,0x3f350000,0x3f35bf80,0xbf350000,0xbf353f80,0x3f350000,0x3f35bf80,0xbf350000,0xbf353f80,
0x3f350000,0x3f35bf80,0xbf350000,0xbf353f80,0xbdc93f35,0x3f75bf0e,0x3ef1bf6d,0xbf463e48,0x3f220000,0x3f62bf7b,0xbe95bec4,0xbf7f3f55,
0xbf7f3f35,0xbe953f55,0x3f62bec4,0x3f22bf7b,0xbf463f80,0x3ef13e48,0x3f75bf6d,0xbdc9bf0e,0x3dc9bf35,0xbf753f0e,0xbef13f6d,0x3f46be48,
0xbf220000,0xbf623f7b,0x3e953ec4,0x3f7fbf55,0x3f7fbf35,0x3e95bf55,0xbf623ec4,0xbf223f7b,0x3f46bf80,0xbef1be48,0xbf753f6d,0x3dc93f0e,
0xbf0e0000,0xbf7b3f6d,0xbe483f35,0x3f55bec4,0x3f55bf80,0xbe48bec4,0xbf7b3f35,0xbf0e3f6d,0x3f0e0000,0x3f7bbf6d,0x3e48bf35,0xbf553ec4,
0xbf553f80,0x3e483ec4,0x3f7bbf35,0x3f0ebf6d,0xbf0e0000,0xbf7b3f6d,0xbe483f35,0x3f55bec4,0x3f55bf80,0xbe48bec4,0xbf7b3f35,0xbf0e3f6d,
0x3f0e0000,0x3f7bbf6d,0x3e48bf35,0xbf553ec4,0xbf553f80,0x3e483ec4,0x3f7bbf35,0x3f0ebf6d,0xbe953f35,0x3f22be48,0x3f7fbf6d,0x3ef1bf55,
0x3f62bf80,0x3dc9bf0e,0xbf463ec4,0xbf753f7b,0xbf753f35,0xbf463f7b,0x3dc93ec4,0x3f62bf0e,0x3ef10000,0x3f7fbf55,0x3f22bf6d,0xbe95be48,
0x3e95bf35,0xbf223e48,0xbf7f3f6d,0xbef13f55,0xbf623f80,0xbdc93f0e,0x3f46bec4,0x3f75bf7b,0x3f75bf35,0x3f46bf7b,0xbdc9bec4,0xbf623f0e,
0xbef10000,0xbf7f3f55,0xbf223f6d,0x3e953e48,0x3ec40000,0x3f6dbf35,0x3f6dbf80,0x3ec4bf35,0xbec40000,0xbf6d3f35,0xbf6d3f80,0xbec43f35,
0x3ec40000,0x3f6dbf35,0x3f6dbf80,0x3ec4bf35,0xbec40000,0xbf6d3f35,0xbf6d3f80,0xbec43f35,0x3ec40000,0x3f6dbf35,0x3f6dbf80,0x3ec4bf35,
0xbec40000,0xbf6d3f35,0xbf6d3f80,0xbec43f35,0x3ec40000,0x3f6dbf35,0x3f6dbf80,0x3ec4bf35,0xbec40000,0xbf6d3f35,0xbf6d3f80,0xbec43f35,
0xbef13f35,0x3dc93e48,0x3f22bec4,0x3f75bf55,0xbe950000,0xbf463f0e,0xbf7f3f6d,0xbf623f7b,0xbf623f35,0xbf7f3f7b,0xbf463f6d,0xbe953f0e,
0x3f75bf80,0x3f22bf55,0x3dc9bec4,0xbef13e48,0x3ef1bf35,0xbdc9be48,0xbf223ec4,0xbf753f55,0x3e950000,0x3f46bf0e,0x3f7fbf6d,0x3f62bf7b,
0x3f62bf35,0x3f7fbf7b,0x3f46bf6d,0x3e95bf0e,0xbf753f80,0xbf223f55,0xbdc93ec4,0x3ef1be48,0xbe480000,0xbf0e3ec4,0xbf553f35,0xbf7b3f6d,
0xbf7b3f80,0xbf553f6d,0xbf0e3f35,0xbe483ec4,0x3e480000,0x3f0ebec4,0x3f55bf35,0x3f7bbf6d,0x3f7bbf80,0x3f55bf6d,0x3f0ebf35,0x3e48bec4,
0xbe480000,0xbf0e3ec4,0xbf553f35,0xbf7b3f6d,0xbf7b3f80,0xbf553f6d,0xbf0e3f35,0xbe483ec4,0x3e480000,0x3f0ebec4,0x3f55bf35,0x3f7bbf6d,
0x3f7bbf80,0x3f55bf6d,0x3f0ebf35,0x3e48bec4,0xbf223f35,0xbef13f0e,0xbe953ec4,0xbdc93e48,0xbf7f3f80,0xbf753f7b,0xbf623f6d,0xbf463f55,
0xbf463f35,0xbf623f55,0xbf753f6d,0xbf7f3f7b,0xbdc90000,0xbe953e48,0xbef13ec4,0xbf223f0e,0x3f22bf35,0x3ef1bf0e,0x3e95bec4,0x3dc9be48,
0x3f7fbf80,0x3f75bf7b,0x3f62bf6d,0x3f46bf55,0x3f46bf35,0x3f62bf55,0x3f75bf6d,0x3f7fbf7b,0x3dc90000,0x3e95be48,0x3ef1bec4,0x3f22bf0e,
0x0,0x0,0x0,0x0,0x0,0x0,0x0,0x0,0x0,0x0,0x0,0x0,
0x0,0x0,0x0,0x0,0x0,0x0,0x0,0x0,0x0,0x0,0x0,0x0,
0x0,0x0,0x0,0x0,0x0,0x0,0x0,0x0,0xbf463f35,0xbf623f55,0xbf753f6d,0xbf7f3f7b,
0xbdc90000,0xbe953e48,0xbef13ec4,0xbf223f0e,0xbf223f35,0xbef13f0e,0xbe953ec4,0xbdc93e48,0xbf7f3f80,0xbf753f7b,0xbf623f6d,0xbf463f55,
0x3f46bf35,0x3f62bf55,0x3f75bf6d,0x3f7fbf7b,0x3dc90000,0x3e95be48,0x3ef1bec4,0x3f22bf0e,0x3f22bf35,0x3ef1bf0e,0x3e95bec4,0x3dc9be48,
0x3f7fbf80,0x3f75bf7b,0x3f62bf6d,0x3f46bf55,0x3e480000,0x3f0ebec4,0x3f55bf35,0x3f7bbf6d,0x3f7bbf80,0x3f55bf6d,0x3f0ebf35,0x3e48bec4,
0xbe480000,0xbf0e3ec4,0xbf553f35,0xbf7b3f6d,0xbf7b3f80,0xbf553f6d,0xbf0e3f35,0xbe483ec4,0x3e480000,0x3f0ebec4,0x3f55bf35,0x3f7bbf6d,
0x3f7bbf80,0x3f55bf6d,0x3f0ebf35,0x3e48bec4,0xbe480000,0xbf0e3ec4,0xbf553f35,0xbf7b3f6d,0xbf7b3f80,0xbf553f6d,0xbf0e3f35,0xbe483ec4,
0xbf623f35,0xbf7f3f7b,0xbf463f6d,0xbe953f0e,0x3f75bf80,0x3f22bf55,0x3dc9bec4,0xbef13e48,0xbef13f35,0x3dc93e48,0x3f22bec4,0x3f75bf55,
0xbe950000,0xbf463f0e,0xbf7f3f6d,0xbf623f7b,0x3f62bf35,0x3f7fbf7b,0x3f46bf6d,0x3e95bf0e,0xbf753f80,0xbf223f55,0xbdc93ec4,0x3ef1be48,
0x3ef1bf35,0xbdc9be48,0xbf223ec4,0xbf753f55,0x3e950000,0x3f46bf0e,0x3f7fbf6d,0x3f62bf7b,0xbec40000,0xbf6d3f35,0xbf6d3f80,0xbec43f35,
0x3ec40000,0x3f6dbf35,0x3f6dbf80,0x3ec4bf35,0xbec40000,0xbf6d3f35,0xbf6d3f80,0xbec43f35,0x3ec40000,0x3f6dbf35,0x3f6dbf80,0x3ec4bf35,
0xbec40000,0xbf6d3f35,0xbf6d3f80,0xbec43f35,0x3ec40000,0x3f6dbf35,0x3f6dbf80,0x3ec4bf35,0xbec40000,0xbf6d3f35,0xbf6d3f80,0xbec43f35,
0x3ec40000,0x3f6dbf35,0x3f6dbf80,0x3ec4bf35,0xbf753f35,0xbf463f7b,0x3dc93ec4,0x3f62bf0e,0x3ef10000,0x3f7fbf55,0x3f22bf6d,0xbe95be48,
0xbe953f35,0x3f22be48,0x3f7fbf6d,0x3ef1bf55,0x3f62bf80,0x3dc9bf0e,0xbf463ec4,0xbf753f7b,0x3f75bf35,0x3f46bf7b,0xbdc9bec4,0xbf623f0e,
0xbef10000,0xbf7f3f55,0xbf223f6d,0x3e953e48,0x3e95bf35,0xbf223e48,0xbf7f3f6d,0xbef13f55,0xbf623f80,0xbdc93f0e,0x3f46bec4,0x3f75bf7b,
0x3f0e0000,0x3f7bbf6d,0x3e48bf35,0xbf553ec4,0xbf553f80,0x3e483ec4,0x3f7bbf35,0x3f0ebf6d,0xbf0e0000,0xbf7b3f6d,0xbe483f35,0x3f55bec4,
0x3f55bf80,0xbe48bec4,0xbf7b3f35,0xbf0e3f6d,0x3f0e0000,0x3f7bbf6d,0x3e48bf35,0xbf553ec4,0xbf553f80,0x3e483ec4,0x3f7bbf35,0x3f0ebf6d,
0xbf0e0000,0xbf7b3f6d,0xbe483f35,0x3f55bec4,0x3f55bf80,0xbe48bec4,0xbf7b3f35,0xbf0e3f6d,0xbf7f3f35,0xbe953f55,0x3f62bec4,0x3f22bf7b,
0xbf463f80,0x3ef13e48,0x3f75bf6d,0xbdc9bf0e,0xbdc93f35,0x3f75bf0e,0x3ef1bf6d,0xbf463e48,0x3f220000,0x3f62bf7b,0xbe95bec4,0xbf7f3f55,
0x3f7fbf35,0x3e95bf55,0xbf623ec4,0xbf223f7b,0x3f46bf80,0xbef1be48,0xbf753f6d,0x3dc93f0e,0x3dc9bf35,0xbf753f0e,0xbef13f6d,0x3f46be48,
0xbf220000,0xbf623f7b,0x3e953ec4,0x3f7fbf55,0xbf350000,0xbf353f80,0x3f350000,0x3f35bf80,0xbf350000,0xbf353f80,0x3f350000,0x3f35bf80,
0xbf350000,0xbf353f80,0x3f350000,0x3f35bf80,0xbf350000,0xbf353f80,0x3f350000,0x3f35bf80,0xbf350000,0xbf353f80,0x3f350000,0x3f35bf80,
0xbf350000,0xbf353f80,0x3f350000,0x3f35bf80,0xbf350000,0xbf353f80,0x3f350000,0x3f35bf80,0xbf350000,0xbf353f80,0x3f350000,0x3f35bf80,
0xbf7f3f35,0x3e953f0e,0x3f62bf6d,0xbf22be48,0xbf460000,0xbef13f7b,0x3f75bec4,0x3dc9bf55,0x3dc93f35,0x3f75bf55,0xbef1bec4,0xbf463f7b,
0xbf223f80,0x3f62be48,0x3e95bf6d,0xbf7f3f0e,0x3f7fbf35,0xbe95bf0e,0xbf623f6d,0x3f223e48,0x3f460000,0x3ef1bf7b,0xbf753ec4,0xbdc93f55,
0xbdc9bf35,0xbf753f55,0x3ef13ec4,0x3f46bf7b,0x3f22bf80,0xbf623e48,0xbe953f6d,0x3f7fbf0e,0x3f550000,0x3e48bf6d,0xbf7b3f35,0x3f0e3ec4,
0x3f0ebf80,0xbf7b3ec4,0x3e483f35,0x3f55bf6d,0xbf550000,0xbe483f6d,0x3f7bbf35,0xbf0ebec4,0xbf0e3f80,0x3f7bbec4,0xbe48bf35,0xbf553f6d,
0x3f550000,0x3e48bf6d,0xbf7b3f35,0x3f0e3ec4,0x3f0ebf80,0xbf7b3ec4,0x3e483f35,0x3f55bf6d,0xbf550000,0xbe483f6d,0x3f7bbf35,0xbf0ebec4,
0xbf0e3f80,0x3f7bbec4,0xbe48bf35,0xbf553f6d,0xbf753f35,0x3f463e48,0x3dc9bf6d,0xbf623f55,0x3ef1bf80,0xbf7f3f0e,0x3f223ec4,0x3e95bf7b,
0x3e953f35,0x3f22bf7b,0xbf7f3ec4,0x3ef13f0e,0xbf620000,0x3dc93f55,0x3f46bf6d,0xbf753e48,0x3f75bf35,0xbf46be48,0xbdc93f6d,0x3f62bf55,
0xbef13f80,0x3f7fbf0e,0xbf22bec4,0xbe953f7b,0xbe95bf35,0xbf223f7b,0x3f7fbec4,0xbef1bf0e,0x3f620000,0xbdc9bf55,0xbf463f6d,0x3f75be48,
0xbf6d0000,0x3ec43f35,0x3ec4bf80,0xbf6d3f35,0x3f6d0000,0xbec4bf35,0xbec43f80,0x3f6dbf35,0xbf6d0000,0x3ec43f35,0x3ec4bf80,0xbf6d3f35,
0x3f6d0000,0xbec4bf35,0xbec43f80,0x3f6dbf35,0xbf6d0000,0x3ec43f35,0x3ec4bf80,0xbf6d3f35,0x3f6d0000,0xbec4bf35,0xbec43f80,0x3f6dbf35,
0xbf6d0000,0x3ec43f35,0x3ec4bf80,0xbf6d3f35,0x3f6d0000,0xbec4bf35,0xbec43f80,0x3f6dbf35,0xbf623f35,0x3f7fbe48,0xbf46bec4,0x3e953f55,
0x3f750000,0xbf22bf0e,0x3dc93f6d,0x3ef1bf7b,0x3ef13f35,0x3dc9bf7b,0xbf223f6d,0x3f75bf0e,0x3e95bf80,0xbf463f55,0x3f7fbec4,0xbf62be48,
0x3f62bf35,0xbf7f3e48,0x3f463ec4,0xbe95bf55,0xbf750000,0x3f223f0e,0xbdc9bf6d,0xbef13f7b,0xbef1bf35,0xbdc93f7b,0x3f22bf6d,0xbf753f0e,
0xbe953f80,0x3f46bf55,0xbf7f3ec4,0x3f623e48,0x3f7b0000,0xbf55bec4,0x3f0e3f35,0xbe48bf6d,0xbe483f80,0x3f0ebf6d,0xbf553f35,0x3f7bbec4,
0xbf7b0000,0x3f553ec4,0xbf0ebf35,0x3e483f6d,0x3e48bf80,0xbf0e3f6d,0x3f55bf35,0xbf7b3ec4,0x3f7b0000,0xbf55bec4,0x3f0e3f35,0xbe48bf6d,
0xbe483f80,0x3f0ebf6d,0xbf553f35,0x3f7bbec4,0xbf7b0000,0x3f553ec4,0xbf0ebf35,0x3e483f6d,0x3e48bf80,0xbf0e3f6d,0x3f55bf35,0xbf7b3ec4,
0xbf463f35,0x3f62bf0e,0xbf753ec4,0x3f7fbe48,0xbdc93f80,0x3e95bf7b,0xbef13f6d,0x3f22bf55,0x3f223f35,0xbef1bf55,0x3e953f6d,0xbdc9bf7b,
0x3f7f0000,0xbf75be48,0x3f623ec4,0xbf46bf0e,0x3f46bf35,0xbf623f0e,0x3f75bec4,0xbf7f3e48,0x3dc9bf80,0xbe953f7b,0x3ef1bf6d,0xbf223f55,
0xbf22bf35,0x3ef13f55,0xbe95bf6d,0x3dc93f7b,0xbf7f0000,0x3f753e48,0xbf62bec4,0x3f463f0e,0xbf800000,0x3f800000,0xbf800000,0x3f800000,
0xbf800000,0x3f800000,0xbf800000,0x3f800000,0xbf800000,0x3f800000,0xbf800000,0x3f800000,0xbf800000,0x3f800000,0xbf800000,0x3f800000,
0xbf800000,0x3f800000,0xbf800000,0x3f800000,0xbf800000,0x3f800000,0xbf800000,0x3f800000,0xbf800000,0x3f800000,0xbf800000,0x3f800000,
0xbf800000,0x3f800000,0xbf800000,0x3f800000,0xbf223f35,0x3ef1bf55,0xbe953f6d,0x3dc9bf7b,0xbf7f0000,0x3f75be48,0xbf623ec4,0x3f46bf0e,
0x3f463f35,0xbf62bf0e,0x3f753ec4,0xbf7fbe48,0x3dc93f80,0xbe95bf7b,0x3ef13f6d,0xbf22bf55,0x3f22bf35,0xbef13f55,0x3e95bf6d,0xbdc93f7b,
0x3f7f0000,0xbf753e48,0x3f62bec4,0xbf463f0e,0xbf46bf35,0x3f623f0e,0xbf75bec4,0x3f7f3e48,0xbdc9bf80,0x3e953f7b,0xbef1bf6d,0x3f223f55,
0x3f7b0000,0xbf553ec4,0x3f0ebf35,0xbe483f6d,0xbe48bf80,0x3f0e3f6d,0xbf55bf35,0x3f7b3ec4,0xbf7b0000,0x3f55bec4,0xbf0e3f35,0x3e48bf6d,
0x3e483f80,0xbf0ebf6d,0x3f553f35,0xbf7bbec4,0x3f7b0000,0xbf553ec4,0x3f0ebf35,0xbe483f6d,0xbe48bf80,0x3f0e3f6d,0xbf55bf35,0x3f7b3ec4,
0xbf7b0000,0x3f55bec4,0xbf0e3f35,0x3e48bf6d,0x3e483f80,0xbf0ebf6d,0x3f553f35,0xbf7bbec4,0xbef13f35,0xbdc9bf7b,0x3f223f6d,0xbf75bf0e,
0xbe95bf80,0x3f463f55,0xbf7fbec4,0x3f62be48,0x3f623f35,0xbf7fbe48,0x3f46bec4,0xbe953f55,0xbf750000,0x3f22bf0e,0xbdc93f6d,0xbef1bf7b,
0x3ef1bf35,0x3dc93f7b,0xbf22bf6d,0x3f753f0e,0x3e953f80,0xbf46bf55,0x3f7f3ec4,0xbf623e48,0xbf62bf35,0x3f7f3e48,0xbf463ec4,0x3e95bf55,
0x3f750000,0xbf223f0e,0x3dc9bf6d,0x3ef13f7b,0xbf6d0000,0x3ec4bf35,0x3ec43f80,0xbf6dbf35,0x3f6d0000,0xbec43f35,0xbec4bf80,0x3f6d3f35,
0xbf6d0000,0x3ec4bf35,0x3ec43f80,0xbf6dbf35,0x3f6d0000,0xbec43f35,0xbec4bf80,0x3f6d3f35,0xbf6d0000,0x3ec4bf35,0x3ec43f80,0xbf6dbf35,
0x3f6d0000,0xbec43f35,0xbec4bf80,0x3f6d3f35,0xbf6d0000,0x3ec4bf35,0x3ec43f80,0xbf6dbf35,0x3f6d0000,0xbec43f35,0xbec4bf80,0x3f6d3f35,
0xbe953f35,0xbf22bf7b,0x3f7f3ec4,0xbef13f0e,0x3f620000,0xbdc93f55,0xbf46bf6d,0x3f753e48,0x3f753f35,0xbf463e48,0xbdc9bf6d,0x3f623f55,
0xbef1bf80,0x3f7f3f0e,0xbf223ec4,0xbe95bf7b,0x3e95bf35,0x3f223f7b,0xbf7fbec4,0x3ef1bf0e,0xbf620000,0x3dc9bf55,0x3f463f6d,0xbf75be48,
0xbf75bf35,0x3f46be48,0x3dc93f6d,0xbf62bf55,0x3ef13f80,0xbf7fbf0e,0x3f22bec4,0x3e953f7b,0x3f550000,0x3e483f6d,0xbf7bbf35,0x3f0ebec4,
0x3f0e3f80,0xbf7bbec4,0x3e48bf35,0x3f553f6d,0xbf550000,0xbe48bf6d,0x3f7b3f35,0xbf0e3ec4,0xbf0ebf80,0x3f7b3ec4,0xbe483f35,0xbf55bf6d,
0x3f550000,0x3e483f6d,0xbf7bbf35,0x3f0ebec4,0x3f0e3f80,0xbf7bbec4,0x3e48bf35,0x3f553f6d,0xbf550000,0xbe48bf6d,0x3f7b3f35,0xbf0e3ec4,
0xbf0ebf80,0x3f7b3ec4,0xbe483f35,0xbf55bf6d,0xbdc93f35,0xbf75bf55,0x3ef1bec4,0x3f463f7b,0x3f223f80,0xbf62be48,0xbe95bf6d,0x3f7f3f0e,
0x3f7f3f35,0xbe953f0e,0xbf62bf6d,0x3f22be48,0x3f460000,0x3ef13f7b,0xbf75bec4,0xbdc9bf55,0x3dc9bf35,0x3f753f55,0xbef13ec4,0xbf46bf7b,
0xbf22bf80,0x3f623e48,0x3e953f6d,0xbf7fbf0e,0xbf7fbf35,0x3e95bf0e,0x3f623f6d,0xbf223e48,0xbf460000,0xbef1bf7b,0x3f753ec4,0x3dc93f55,
0xbf350000,0xbf35bf80,0x3f350000,0x3f353f80,0xbf350000,0xbf35bf80,0x3f350000,0x3f353f80,0xbf350000,0xbf35bf80,0x3f350000,0x3f353f80,
0xbf350000,0xbf35bf80,0x3f350000,0x3f353f80,0xbf350000,0xbf35bf80,0x3f350000,0x3f353f80,0xbf350000,0xbf35bf80,0x3f350000,0x3f353f80,
0xbf350000,0xbf35bf80,0x3f350000,0x3f353f80,0xbf350000,0xbf35bf80,0x3f350000,0x3f353f80,0x3dc93f35,0xbf75bf0e,0xbef1bf6d,0x3f463e48,
0xbf220000,0xbf62bf7b,0x3e95bec4,0x3f7f3f55,0x3f7f3f35,0x3e953f55,0xbf62bec4,0xbf22bf7b,0x3f463f80,0xbef13e48,0xbf75bf6d,0x3dc9bf0e,
0xbdc9bf35,0x3f753f0e,0x3ef13f6d,0xbf46be48,0x3f220000,0x3f623f7b,0xbe953ec4,0xbf7fbf55,0xbf7fbf35,0xbe95bf55,0x3f623ec4,0x3f223f7b,
0xbf46bf80,0x3ef1be48,0x3f753f6d,0xbdc93f0e,0x3f0e0000,0x3f7b3f6d,0x3e483f35,0xbf55bec4,0xbf55bf80,0x3e48bec4,0x3f7b3f35,0x3f0e3f6d,
0xbf0e0000,0xbf7bbf6d,0xbe48bf35,0x3f553ec4,0x3f553f80,0xbe483ec4,0xbf7bbf35,0xbf0ebf6d,0x3f0e0000,0x3f7b3f6d,0x3e483f35,0xbf55bec4,
0xbf55bf80,0x3e48bec4,0x3f7b3f35,0x3f0e3f6d,0xbf0e0000,0xbf7bbf6d,0xbe48bf35,0x3f553ec4,0x3f553f80,0xbe483ec4,0xbf7bbf35,0xbf0ebf6d,
0x3e953f35,0xbf22be48,0xbf7fbf6d,0xbef1bf55,0xbf62bf80,0xbdc9bf0e,0x3f463ec4,0x3f753f7b,0x3f753f35,0x3f463f7b,0xbdc93ec4,0xbf62bf0e,
0xbef10000,0xbf7fbf55,0xbf22bf6d,0x3e95be48,0xbe95bf35,0x3f223e48,0x3f7f3f6d,0x3ef13f55,0x3f623f80,0x3dc93f0e,0xbf46bec4,0xbf75bf7b,
0xbf75bf35,0xbf46bf7b,0x3dc9bec4,0x3f623f0e,0x3ef10000,0x3f7f3f55,0x3f223f6d,0xbe953e48,0xbec40000,0xbf6dbf35,0xbf6dbf80,0xbec4bf35,
0x3ec40000,0x3f6d3f35,0x3f6d3f80,0x3ec43f35,0xbec40000,0xbf6dbf35,0xbf6dbf80,0xbec4bf35,0x3ec40000,0x3f6d3f35,0x3f6d3f80,0x3ec43f35,
0xbec40000,0xbf6dbf35,0xbf6dbf80,0xbec4bf35,0x3ec40000,0x3f6d3f35,0x3f6d3f80,0x3ec43f35,0xbec40000,0xbf6dbf35,0xbf6dbf80,0xbec4bf35,
0x3ec40000,0x3f6d3f35,0x3f6d3f80,0x3ec43f35,0x3ef13f35,0xbdc93e48,0xbf22bec4,0xbf75bf55,0x3e950000,0x3f463f0e,0x3f7f3f6d,0x3f623f7b,
0x3f623f35,0x3f7f3f7b,0x3f463f6d,0x3e953f0e,0xbf75bf80,0xbf22bf55,0xbdc9bec4,0x3ef13e48,0xbef1bf35,0x3dc9be48,0x3f223ec4,0x3f753f55,
0xbe950000,0xbf46bf0e,0xbf7fbf6d,0xbf62bf7b,0xbf62bf35,0xbf7fbf7b,0xbf46bf6d,0xbe95bf0e,0x3f753f80,0x3f223f55,0x3dc93ec4,0xbef1be48,
0x3e480000,0x3f0e3ec4,0x3f553f35,0x3f7b3f6d,0x3f7b3f80,0x3f553f6d,0x3f0e3f35,0x3e483ec4,0xbe480000,0xbf0ebec4,0xbf55bf35,0xbf7bbf6d,
0xbf7bbf80,0xbf55bf6d,0xbf0ebf35,0xbe48bec4,0x3e480000,0x3f0e3ec4,0x3f553f35,0x3f7b3f6d,0x3f7b3f80,0x3f553f6d,0x3f0e3f35,0x3e483ec4,
0xbe480000,0xbf0ebec4,0xbf55bf35,0xbf7bbf6d,0xbf7bbf80,0xbf55bf6d,0xbf0ebf35,0xbe48bec4,0x3f223f35,0x3ef13f0e,0x3e953ec4,0x3dc93e48,
0x3f7f3f80,0x3f753f7b,0x3f623f6d,0x3f463f55,0x3f463f35,0x3f623f55,0x3f753f6d,0x3f7f3f7b,0x3dc90000,0x3e953e48,0x3ef13ec4,0x3f223f0e,
0xbf22bf35,0xbef1bf0e,0xbe95bec4,0xbdc9be48,0xbf7fbf80,0xbf75bf7b,0xbf62bf6d,0xbf46bf55,0xbf46bf35,0xbf62bf55,0xbf75bf6d,0xbf7fbf7b,
0xbdc90000,0xbe95be48,0xbef1bec4,0xbf22bf0e,0x80003f80,0x80003f80,0x80003f80,0x80003f80,0x80003f80,0x80003f80,0x80003f80,0x80003f80,
0x80003f80,0x80003f80,0x80003f80,0x80003f80,0x80003f80,0x80003f80,0x80003f80,0x80003f80,0x80003f80,0x80003f80,0x80003f80,0x80003f80,
0x80003f80,0x80003f80,0x80003f80,0x80003f80,0x80003f80,0x80003f80,0x80003f80,0x80003f80,0x80003f80,0x80003f80,0x80003f80,0x80003f80,
0x3f800000,0x3f800000,0x3f800000,0x3f800000,0x3f800000,0x3f800000,0x3f800000,0x3f800000,0x3f800000,0x3f800000,0x3f800000,0x3f800000,
0x3f800000,0x3f800000,0x3f800000,0x3f800000,0x3f800000,0x3f800000,0x3f800000,0x3f800000,0x3f800000,0x3f800000,0x3f800000,0x3f800000,
0x3f800000,0x3f800000,0x3f800000,0x3f800000,0x3f800000,0x3f800000,0x3f800000,0x3f800000,0xbf800000,0xbf7bbe48,0xbf6dbec4,0xbf55bf0e,
0xbf35bf35,0xbf0ebf55,0xbec4bf6d,0xbe48bf7b,0x80003f80,0xbe483f7b,0xbec43f6d,0xbf0e3f55,0xbf353f35,0xbf553f0e,0xbf6d3ec4,0xbf7b3e48,
0x3f800000,0x3f7b3e48,0x3f6d3ec4,0x3f553f0e,0x3f353f35,0x3f0e3f55,0x3ec43f6d,0x3e483f7b,0x8000bf80,0x3e48bf7b,0x3ec4bf6d,0x3f0ebf55,
0x3f35bf35,0x3f55bf0e,0x3f6dbec4,0x3f7bbe48,0xbf353f35,0xbf553f0e,0xbf6d3ec4,0xbf7b3e48,0x3f80,0xbe483f7b,0xbec43f6d,0xbf0e3f55,
0x3f353f35,0x3f0e3f55,0x3ec43f6d,0x3e483f7b,0x3f800000,0x3f7b3e48,0x3f6d3ec4,0x3f553f0e,0x3f35bf35,0x3f55bf0e,0x3f6dbec4,0x3f7bbe48,
0xbf80,0x3e48bf7b,0x3ec4bf6d,0x3f0ebf55,0xbf35bf35,0xbf0ebf55,0xbec4bf6d,0xbe48bf7b,0xbf800000,0xbf7bbe48,0xbf6dbec4,0xbf55bf0e,
0x80003f80,0xbec43f6d,0xbf353f35,0xbf6d3ec4,0xbf800000,0xbf6dbec4,0xbf35bf35,0xbec4bf6d,0x8000bf80,0x3ec4bf6d,0x3f35bf35,0x3f6dbec4,
0x3f800000,0x3f6d3ec4,0x3f353f35,0x3ec43f6d,0x80003f80,0xbec43f6d,0xbf353f35,0xbf6d3ec4,0xbf800000,0xbf6dbec4,0xbf35bf35,0xbec4bf6d,
0x8000bf80,0x3ec4bf6d,0x3f35bf35,0x3f6dbec4,0x3f800000,0x3f6d3ec4,0x3f353f35,0x3ec43f6d,0x3f80,0xbec43f6d,0xbf353f35,0xbf6d3ec4,
0x3f800000,0x3f6d3ec4,0x3f353f35,0x3ec43f6d,0xbf80,0x3ec4bf6d,0x3f35bf35,0x3f6dbec4,0xbf800000,0xbf6dbec4,0xbf35bf35,0xbec4bf6d,
0x3f80,0xbec43f6d,0xbf353f35,0xbf6d3ec4,0x3f800000,0x3f6d3ec4,0x3f353f35,0x3ec43f6d,0xbf80,0x3ec4bf6d,0x3f35bf35,0x3f6dbec4,
0xbf800000,0xbf6dbec4,0xbf35bf35,0xbec4bf6d,0xbf800000,0xbf55bf0e,0xbec4bf6d,0x3e48bf7b,0x3f35bf35,0x3f7bbe48,0x3f6d3ec4,0x3f0e3f55,
0x8000bf80,0x3f0ebf55,0x3f6dbec4,0x3f7b3e48,0x3f353f35,0x3e483f7b,0xbec43f6d,0xbf553f0e,0x3f800000,0x3f553f0e,0x3ec43f6d,0xbe483f7b,
0xbf353f35,0xbf7b3e48,0xbf6dbec4,0xbf0ebf55,0x80003f80,0xbf0e3f55,0xbf6d3ec4,0xbf7bbe48,0xbf35bf35,0xbe48bf7b,0x3ec4bf6d,0x3f55bf0e,
0xbf35bf35,0xbe48bf7b,0x3ec4bf6d,0x3f55bf0e,0x3f80,0xbf0e3f55,0xbf6d3ec4,0xbf7bbe48,0x3f35bf35,0x3f7bbe48,0x3f6d3ec4,0x3f0e3f55,
0xbf800000,0xbf55bf0e,0xbec4bf6d,0x3e48bf7b,0x3f353f35,0x3e483f7b,0xbec43f6d,0xbf553f0e,0xbf80,0x3f0ebf55,0x3f6dbec4,0x3f7b3e48,
0xbf353f35,0xbf7b3e48,0xbf6dbec4,0xbf0ebf55,0x3f800000,0x3f553f0e,0x3ec43f6d,0xbe483f7b,0x80003f80,0xbf353f35,0xbf800000,0xbf35bf35,
0x8000bf80,0x3f35bf35,0x3f800000,0x3f353f35,0x80003f80,0xbf353f35,0xbf800000,0xbf35bf35,0x8000bf80,0x3f35bf35,0x3f800000,0x3f353f35,
0x80003f80,0xbf353f35,0xbf800000,0xbf35bf35,0x8000bf80,0x3f35bf35,0x3f800000,0x3f353f35,0x80003f80,0xbf353f35,0xbf800000,0xbf35bf35,
0x8000bf80,0x3f35bf35,0x3f800000,0x3f353f35,0xbf800000,0xbf35bf35,0xbf80,0x3f35bf35,0x3f800000,0x3f353f35,0x3f80,0xbf353f35,
0xbf800000,0xbf35bf35,0xbf80,0x3f35bf35,0x3f800000,0x3f353f35,0x3f80,0xbf353f35,0xbf800000,0xbf35bf35,0xbf80,0x3f35bf35,
0x3f800000,0x3f353f35,0x3f80,0xbf353f35,0xbf800000,0xbf35bf35,0xbf80,0x3f35bf35,0x3f800000,0x3f353f35,0x3f80,0xbf353f35,
0xbf800000,0xbf0ebf55,0x3ec4bf6d,0x3f7bbe48,0x3f353f35,0xbe483f7b,0xbf6d3ec4,0xbf55bf0e,0x80003f80,0xbf553f0e,0xbf6dbec4,0xbe48bf7b,
0x3f35bf35,0x3f7b3e48,0x3ec43f6d,0xbf0e3f55,0x3f800000,0x3f0e3f55,0xbec43f6d,0xbf7b3e48,0xbf35bf35,0x3e48bf7b,0x3f6dbec4,0x3f553f0e,
0x8000bf80,0x3f55bf0e,0x3f6d3ec4,0x3e483f7b,0xbf353f35,0xbf7bbe48,0xbec4bf6d,0x3f0ebf55,0x3f35bf35,0x3f7b3e48,0x3ec43f6d,0xbf0e3f55,
0x3f80,0xbf553f0e,0xbf6dbec4,0xbe48bf7b,0xbf35bf35,0x3e48bf7b,0x3f6dbec4,0x3f553f0e,0x3f800000,0x3f0e3f55,0xbec43f6d,0xbf7b3e48,
0xbf353f35,0xbf7bbe48,0xbec4bf6d,0x3f0ebf55,0xbf80,0x3f55bf0e,0x3f6d3ec4,0x3e483f7b,0x3f353f35,0xbe483f7b,0xbf6d3ec4,0xbf55bf0e,
0xbf800000,0xbf0ebf55,0x3ec4bf6d,0x3f7bbe48,0x80003f80,0xbf6d3ec4,0xbf35bf35,0x3ec4bf6d,0x3f800000,0x3ec43f6d,0xbf353f35,0xbf6dbec4,
0x8000bf80,0x3f6dbec4,0x3f353f35,0xbec43f6d,0xbf800000,0xbec4bf6d,0x3f35bf35,0x3f6d3ec4,0x80003f80,0xbf6d3ec4,0xbf35bf35,0x3ec4bf6d,
0x3f800000,0x3ec43f6d,0xbf353f35,0xbf6dbec4,0x8000bf80,0x3f6dbec4,0x3f353f35,0xbec43f6d,0xbf800000,0xbec4bf6d,0x3f35bf35,0x3f6d3ec4,
0xbf80,0x3f6dbec4,0x3f353f35,0xbec43f6d,0x3f800000,0x3ec43f6d,0xbf353f35,0xbf6dbec4,0x3f80,0xbf6d3ec4,0xbf35bf35,0x3ec4bf6d,
0xbf800000,0xbec4bf6d,0x3f35bf35,0x3f6d3ec4,0xbf80,0x3f6dbec4,0x3f353f35,0xbec43f6d,0x3f800000,0x3ec43f6d,0xbf353f35,0xbf6dbec4,
0x3f80,0xbf6d3ec4,0xbf35bf35,0x3ec4bf6d,0xbf800000,0xbec4bf6d,0x3f35bf35,0x3f6d3ec4,0xbf800000,0xbe48bf7b,0x3f6dbec4,0x3f0e3f55,
0xbf353f35,0xbf55bf0e,0x3ec4bf6d,0x3f7b3e48,0x8000bf80,0x3f7bbe48,0x3ec43f6d,0xbf553f0e,0xbf35bf35,0x3f0ebf55,0x3f6d3ec4,0xbe483f7b,
0x3f800000,0x3e483f7b,0xbf6d3ec4,0xbf0ebf55,0x3f35bf35,0x3f553f0e,0xbec43f6d,0xbf7bbe48,0x80003f80,0xbf7b3e48,0xbec4bf6d,0x3f55bf0e,
0x3f353f35,0xbf0e3f55,0xbf6dbec4,0x3e48bf7b,0x3f353f35,0xbf0e3f55,0xbf6dbec4,0x3e48bf7b,0x3f80,0xbf7b3e48,0xbec4bf6d,0x3f55bf0e,
0xbf353f35,0xbf55bf0e,0x3ec4bf6d,0x3f7b3e48,0xbf800000,0xbe48bf7b,0x3f6dbec4,0x3f0e3f55,0xbf35bf35,0x3f0ebf55,0x3f6d3ec4,0xbe483f7b,
0xbf80,0x3f7bbe48,0x3ec43f6d,0xbf553f0e,0x3f35bf35,0x3f553f0e,0xbec43f6d,0xbf7bbe48,0x3f800000,0x3e483f7b,0xbf6d3ec4,0xbf0ebf55,
0x80003f80,0xbf800000,0x8000bf80,0x3f800000,0x80003f80,0xbf800000,0x8000bf80,0x3f800000,0x80003f80,0xbf800000,0x8000bf80,0x3f800000,
0x80003f80,0xbf800000,0x8000bf80,0x3f800000,0x80003f80,0xbf800000,0x8000bf80,0x3f800000,0x80003f80,0xbf800000,0x8000bf80,0x3f800000,
0x80003f80,0xbf800000,0x8000bf80,0x3f800000,0x80003f80,0xbf800000,0x8000bf80,0x3f800000,0x3f800000,0x3f80,0xbf800000,0xbf80,
0x3f800000,0x3f80,0xbf800000,0xbf80,0x3f800000,0x3f80,0xbf800000,0xbf80,0x3f800000,0x3f80,0xbf800000,0xbf80,
0x3f800000,0x3f80,0xbf800000,0xbf80,0x3f800000,0x3f80,0xbf800000,0xbf80,0x3f800000,0x3f80,0xbf800000,0xbf80,
0x3f800000,0x3f80,0xbf800000,0xbf80,0xbf800000,0x3e48bf7b,0x3f6d3ec4,0xbf0e3f55,0xbf35bf35,0x3f55bf0e,0x3ec43f6d,0xbf7b3e48,
0x80003f80,0xbf7bbe48,0x3ec4bf6d,0x3f553f0e,0xbf353f35,0xbf0ebf55,0x3f6dbec4,0x3e483f7b,0x3f800000,0xbe483f7b,0xbf6dbec4,0x3f0ebf55,
0x3f353f35,0xbf553f0e,0xbec4bf6d,0x3f7bbe48,0x8000bf80,0x3f7b3e48,0xbec43f6d,0xbf55bf0e,0x3f35bf35,0x3f0e3f55,0xbf6d3ec4,0xbe48bf7b,
0xbf353f35,0xbf0ebf55,0x3f6dbec4,0x3e483f7b,0x3f80,0xbf7bbe48,0x3ec4bf6d,0x3f553f0e,0x3f353f35,0xbf553f0e,0xbec4bf6d,0x3f7bbe48,
0x3f800000,0xbe483f7b,0xbf6dbec4,0x3f0ebf55,0x3f35bf35,0x3f0e3f55,0xbf6d3ec4,0xbe48bf7b,0xbf80,0x3f7b3e48,0xbec43f6d,0xbf55bf0e,
0xbf35bf35,0x3f55bf0e,0x3ec43f6d,0xbf7b3e48,0xbf800000,0x3e48bf7b,0x3f6d3ec4,0xbf0e3f55,0x80003f80,0xbf6dbec4,0x3f35bf35,0x3ec43f6d,
0xbf800000,0x3ec4bf6d,0x3f353f35,0xbf6d3ec4,0x8000bf80,0x3f6d3ec4,0xbf353f35,0xbec4bf6d,0x3f800000,0xbec43f6d,0xbf35bf35,0x3f6dbec4,
0x80003f80,0xbf6dbec4,0x3f35bf35,0x3ec43f6d,0xbf800000,0x3ec4bf6d,0x3f353f35,0xbf6d3ec4,0x8000bf80,0x3f6d3ec4,0xbf353f35,0xbec4bf6d,
0x3f800000,0xbec43f6d,0xbf35bf35,0x3f6dbec4,0x3f80,0xbf6dbec4,0x3f35bf35,0x3ec43f6d,0x3f800000,0xbec43f6d,0xbf35bf35,0x3f6dbec4,
0xbf80,0x3f6d3ec4,0xbf353f35,0xbec4bf6d,0xbf800000,0x3ec4bf6d,0x3f353f35,0xbf6d3ec4,0x3f80,0xbf6dbec4,0x3f35bf35,0x3ec43f6d,
0x3f800000,0xbec43f6d,0xbf35bf35,0x3f6dbec4,0xbf80,0x3f6d3ec4,0xbf353f35,0xbec4bf6d,0xbf800000,0x3ec4bf6d,0x3f353f35,0xbf6d3ec4,
0xbf800000,0x3f0ebf55,0x3ec43f6d,0xbf7bbe48,0x3f35bf35,0x3e483f7b,0xbf6dbec4,0x3f55bf0e,0x8000bf80,0x3f553f0e,0xbf6d3ec4,0x3e48bf7b,
0x3f353f35,0xbf7b3e48,0x3ec4bf6d,0x3f0e3f55,0x3f800000,0xbf0e3f55,0xbec4bf6d,0x3f7b3e48,0xbf353f35,0xbe48bf7b,0x3f6d3ec4,0xbf553f0e,
0x80003f80,0xbf55bf0e,0x3f6dbec4,0xbe483f7b,0xbf35bf35,0x3f7bbe48,0xbec43f6d,0xbf0ebf55,0xbf35bf35,0x3f7bbe48,0xbec43f6d,0xbf0ebf55,
0x3f80,0xbf55bf0e,0x3f6dbec4,0xbe483f7b,0x3f35bf35,0x3e483f7b,0xbf6dbec4,0x3f55bf0e,0xbf800000,0x3f0ebf55,0x3ec43f6d,0xbf7bbe48,
0x3f353f35,0xbf7b3e48,0x3ec4bf6d,0x3f0e3f55,0xbf80,0x3f553f0e,0xbf6d3ec4,0x3e48bf7b,0xbf353f35,0xbe48bf7b,0x3f6d3ec4,0xbf553f0e,
0x3f800000,0xbf0e3f55,0xbec4bf6d,0x3f7b3e48,0x80003f80,0xbf35bf35,0x3f800000,0xbf353f35,0x8000bf80,0x3f353f35,0xbf800000,0x3f35bf35,
0x80003f80,0xbf35bf35,0x3f800000,0xbf353f35,0x8000bf80,0x3f353f35,0xbf800000,0x3f35bf35,0x80003f80,0xbf35bf35,0x3f800000,0xbf353f35,
0x8000bf80,0x3f353f35,0xbf800000,0x3f35bf35,0x80003f80,0xbf35bf35,0x3f800000,0xbf353f35,0x8000bf80,0x3f353f35,0xbf800000,0x3f35bf35,
0xbf800000,0x3f35bf35,0x3f80,0xbf35bf35,0x3f800000,0xbf353f35,0xbf80,0x3f353f35,0xbf800000,0x3f35bf35,0x3f80,0xbf35bf35,
0x3f800000,0xbf353f35,0xbf80,0x3f353f35,0xbf800000,0x3f35bf35,0x3f80,0xbf35bf35,0x3f800000,0xbf353f35,0xbf80,0x3f353f35,
0xbf800000,0x3f35bf35,0x3f80,0xbf35bf35,0x3f800000,0xbf353f35,0xbf80,0x3f353f35,0xbf800000,0x3f55bf0e,0xbec43f6d,0xbe48bf7b,
0x3f353f35,0xbf7bbe48,0x3f6dbec4,0xbf0e3f55,0x80003f80,0xbf0ebf55,0x3f6d3ec4,0xbf7b3e48,0x3f35bf35,0xbe483f7b,0xbec4bf6d,0x3f553f0e,
0x3f800000,0xbf553f0e,0x3ec4bf6d,0x3e483f7b,0xbf35bf35,0x3f7b3e48,0xbf6d3ec4,0x3f0ebf55,0x8000bf80,0x3f0e3f55,0xbf6dbec4,0x3f7bbe48,
0xbf353f35,0x3e48bf7b,0x3ec43f6d,0xbf55bf0e,0x3f35bf35,0xbe483f7b,0xbec4bf6d,0x3f553f0e,0x3f80,0xbf0ebf55,0x3f6d3ec4,0xbf7b3e48,
0xbf35bf35,0x3f7b3e48,0xbf6d3ec4,0x3f0ebf55,0x3f800000,0xbf553f0e,0x3ec4bf6d,0x3e483f7b,0xbf353f35,0x3e48bf7b,0x3ec43f6d,0xbf55bf0e,
0xbf80,0x3f0e3f55,0xbf6dbec4,0x3f7bbe48,0x3f353f35,0xbf7bbe48,0x3f6dbec4,0xbf0e3f55,0xbf800000,0x3f55bf0e,0xbec43f6d,0xbe48bf7b,
0x80003f80,0xbec4bf6d,0x3f353f35,0xbf6dbec4,0x3f800000,0xbf6d3ec4,0x3f35bf35,0xbec43f6d,0x8000bf80,0x3ec43f6d,0xbf35bf35,0x3f6d3ec4,
0xbf800000,0x3f6dbec4,0xbf353f35,0x3ec4bf6d,0x80003f80,0xbec4bf6d,0x3f353f35,0xbf6dbec4,0x3f800000,0xbf6d3ec4,0x3f35bf35,0xbec43f6d,
0x8000bf80,0x3ec43f6d,0xbf35bf35,0x3f6d3ec4,0xbf800000,0x3f6dbec4,0xbf353f35,0x3ec4bf6d,0xbf80,0x3ec43f6d,0xbf35bf35,0x3f6d3ec4,
0x3f800000,0xbf6d3ec4,0x3f35bf35,0xbec43f6d,0x3f80,0xbec4bf6d,0x3f353f35,0xbf6dbec4,0xbf800000,0x3f6dbec4,0xbf353f35,0x3ec4bf6d,
0xbf80,0x3ec43f6d,0xbf35bf35,0x3f6d3ec4,0x3f800000,0xbf6d3ec4,0x3f35bf35,0xbec43f6d,0x3f80,0xbec4bf6d,0x3f353f35,0xbf6dbec4,
0xbf800000,0x3f6dbec4,0xbf353f35,0x3ec4bf6d,0xbf800000,0x3f7bbe48,0xbf6d3ec4,0x3f55bf0e,0xbf353f35,0x3f0ebf55,0xbec43f6d,0x3e48bf7b,
0x8000bf80,0x3e483f7b,0xbec4bf6d,0x3f0e3f55,0xbf35bf35,0x3f553f0e,0xbf6dbec4,0x3f7b3e48,0x3f800000,0xbf7b3e48,0x3f6dbec4,0xbf553f0e,
0x3f35bf35,0xbf0e3f55,0x3ec4bf6d,0xbe483f7b,0x80003f80,0xbe48bf7b,0x3ec43f6d,0xbf0ebf55,0x3f353f35,0xbf55bf0e,0x3f6d3ec4,0xbf7bbe48,
0x3f353f35,0xbf55bf0e,0x3f6d3ec4,0xbf7bbe48,0x3f80,0xbe48bf7b,0x3ec43f6d,0xbf0ebf55,0xbf353f35,0x3f0ebf55,0xbec43f6d,0x3e48bf7b,
0xbf800000,0x3f7bbe48,0xbf6d3ec4,0x3f55bf0e,0xbf35bf35,0x3f553f0e,0xbf6dbec4,0x3f7b3e48,0xbf80,0x3e483f7b,0xbec4bf6d,0x3f0e3f55,
0x3f35bf35,0xbf0e3f55,0x3ec4bf6d,0xbe483f7b,0x3f800000,0xbf7b3e48,0x3f6dbec4,0xbf553f0e,0x80003f80,0x8000bf80,0x80003f80,0x8000bf80,
0x80003f80,0x8000bf80,0x80003f80,0x8000bf80,0x80003f80,0x8000bf80,0x80003f80,0x8000bf80,0x80003f80,0x8000bf80,0x80003f80,0x8000bf80,
0x80003f80,0x8000bf80,0x80003f80,0x8000bf80,0x80003f80,0x8000bf80,0x80003f80,0x8000bf80,0x80003f80,0x8000bf80,0x80003f80,0x8000bf80,
0x80003f80,0x8000bf80,0x80003f80,0x8000bf80,0x3f800000,0xbf800000,0x3f800000,0xbf800000,0x3f800000,0xbf800000,0x3f800000,0xbf800000,
0x3f800000,0xbf800000,0x3f800000,0xbf800000,0x3f800000,0xbf800000,0x3f800000,0xbf800000,0x3f800000,0xbf800000,0x3f800000,0xbf800000,
0x3f800000,0xbf800000,0x3f800000,0xbf800000,0x3f800000,0xbf800000,0x3f800000,0xbf800000,0x3f800000,0xbf800000,0x3f800000,0xbf800000,
0xbf800000,0x3f7b3e48,0xbf6dbec4,0x3f553f0e,0xbf35bf35,0x3f0e3f55,0xbec4bf6d,0x3e483f7b,0x80003f80,0x3e48bf7b,0xbec43f6d,0x3f0ebf55,
0xbf353f35,0x3f55bf0e,0xbf6d3ec4,0x3f7bbe48,0x3f800000,0xbf7bbe48,0x3f6d3ec4,0xbf55bf0e,0x3f353f35,0xbf0ebf55,0x3ec43f6d,0xbe48bf7b,
0x8000bf80,0xbe483f7b,0x3ec4bf6d,0xbf0e3f55,0x3f35bf35,0xbf553f0e,0x3f6dbec4,0xbf7b3e48,0xbf353f35,0x3f55bf0e,0xbf6d3ec4,0x3f7bbe48,
0x3f80,0x3e48bf7b,0xbec43f6d,0x3f0ebf55,0x3f353f35,0xbf0ebf55,0x3ec43f6d,0xbe48bf7b,0x3f800000,0xbf7bbe48,0x3f6d3ec4,0xbf55bf0e,
0x3f35bf35,0xbf553f0e,0x3f6dbec4,0xbf7b3e48,0xbf80,0xbe483f7b,0x3ec4bf6d,0xbf0e3f55,0xbf35bf35,0x3f0e3f55,0xbec4bf6d,0x3e483f7b,
0xbf800000,0x3f7b3e48,0xbf6dbec4,0x3f553f0e,0x80003f80,0x3ec4bf6d,0xbf353f35,0x3f6dbec4,0xbf800000,0x3f6d3ec4,0xbf35bf35,0x3ec43f6d,
0x8000bf80,0xbec43f6d,0x3f35bf35,0xbf6d3ec4,0x3f800000,0xbf6dbec4,0x3f353f35,0xbec4bf6d,0x80003f80,0x3ec4bf6d,0xbf353f35,0x3f6dbec4,
0xbf800000,0x3f6d3ec4,0xbf35bf35,0x3ec43f6d,0x8000bf80,0xbec43f6d,0x3f35bf35,0xbf6d3ec4,0x3f800000,0xbf6dbec4,0x3f353f35,0xbec4bf6d,
0x3f80,0x3ec4bf6d,0xbf353f35,0x3f6dbec4,0x3f800000,0xbf6dbec4,0x3f353f35,0xbec4bf6d,0xbf80,0xbec43f6d,0x3f35bf35,0xbf6d3ec4,
0xbf800000,0x3f6d3ec4,0xbf35bf35,0x3ec43f6d,0x3f80,0x3ec4bf6d,0xbf353f35,0x3f6dbec4,0x3f800000,0xbf6dbec4,0x3f353f35,0xbec4bf6d,
0xbf80,0xbec43f6d,0x3f35bf35,0xbf6d3ec4,0xbf800000,0x3f6d3ec4,0xbf35bf35,0x3ec43f6d,0xbf800000,0x3f553f0e,0xbec4bf6d,0xbe483f7b,
0x3f35bf35,0xbf7b3e48,0x3f6d3ec4,0xbf0ebf55,0x8000bf80,0xbf0e3f55,0x3f6dbec4,0xbf7bbe48,0x3f353f35,0xbe48bf7b,0xbec43f6d,0x3f55bf0e,
0x3f800000,0xbf55bf0e,0x3ec43f6d,0x3e48bf7b,0xbf353f35,0x3f7bbe48,0xbf6dbec4,0x3f0e3f55,0x80003f80,0x3f0ebf55,0xbf6d3ec4,0x3f7b3e48,
0xbf35bf35,0x3e483f7b,0x3ec4bf6d,0xbf553f0e,0xbf35bf35,0x3e483f7b,0x3ec4bf6d,0xbf553f0e,0x3f80,0x3f0ebf55,0xbf6d3ec4,0x3f7b3e48,
0x3f35bf35,0xbf7b3e48,0x3f6d3ec4,0xbf0ebf55,0xbf800000,0x3f553f0e,0xbec4bf6d,0xbe483f7b,0x3f353f35,0xbe48bf7b,0xbec43f6d,0x3f55bf0e,
0xbf80,0xbf0e3f55,0x3f6dbec4,0xbf7bbe48,0xbf353f35,0x3f7bbe48,0xbf6dbec4,0x3f0e3f55,0x3f800000,0xbf55bf0e,0x3ec43f6d,0x3e48bf7b,
0x80003f80,0x3f35bf35,0xbf800000,0x3f353f35,0x8000bf80,0xbf353f35,0x3f800000,0xbf35bf35,0x80003f80,0x3f35bf35,0xbf800000,0x3f353f35,
0x8000bf80,0xbf353f35,0x3f800000,0xbf35bf35,0x80003f80,0x3f35bf35,0xbf800000,0x3f353f35,0x8000bf80,0xbf353f35,0x3f800000,0xbf35bf35,
0x80003f80,0x3f35bf35,0xbf800000,0x3f353f35,0x8000bf80,0xbf353f35,0x3f800000,0xbf35bf35,0xbf800000,0x3f353f35,0xbf80,0xbf353f35,
0x3f800000,0xbf35bf35,0x3f80,0x3f35bf35,0xbf800000,0x3f353f35,0xbf80,0xbf353f35,0x3f800000,0xbf35bf35,0x3f80,0x3f35bf35,
0xbf800000,0x3f353f35,0xbf80,0xbf353f35,0x3f800000,0xbf35bf35,0x3f80,0x3f35bf35,0xbf800000,0x3f353f35,0xbf80,0xbf353f35,
0x3f800000,0xbf35bf35,0x3f80,0x3f35bf35,0xbf800000,0x3f0e3f55,0x3ec4bf6d,0xbf7b3e48,0x3f353f35,0x3e48bf7b,0xbf6d3ec4,0x3f553f0e,
0x80003f80,0x3f55bf0e,0xbf6dbec4,0x3e483f7b,0x3f35bf35,0xbf7bbe48,0x3ec43f6d,0x3f0ebf55,0x3f800000,0xbf0ebf55,0xbec43f6d,0x3f7bbe48,
0xbf35bf35,0xbe483f7b,0x3f6dbec4,0xbf55bf0e,0x8000bf80,0xbf553f0e,0x3f6d3ec4,0xbe48bf7b,0xbf353f35,0x3f7b3e48,0xbec4bf6d,0xbf0e3f55,
0x3f35bf35,0xbf7bbe48,0x3ec43f6d,0x3f0ebf55,0x3f80,0x3f55bf0e,0xbf6dbec4,0x3e483f7b,0xbf35bf35,0xbe483f7b,0x3f6dbec4,0xbf55bf0e,
0x3f800000,0xbf0ebf55,0xbec43f6d,0x3f7bbe48,0xbf353f35,0x3f7b3e48,0xbec4bf6d,0xbf0e3f55,0xbf80,0xbf553f0e,0x3f6d3ec4,0xbe48bf7b,
0x3f353f35,0x3e48bf7b,0xbf6d3ec4,0x3f553f0e,0xbf800000,0x3f0e3f55,0x3ec4bf6d,0xbf7b3e48,0x80003f80,0x3f6dbec4,0xbf35bf35,0xbec43f6d,
0x3f800000,0xbec4bf6d,0xbf353f35,0x3f6d3ec4,0x8000bf80,0xbf6d3ec4,0x3f353f35,0x3ec4bf6d,0xbf800000,0x3ec43f6d,0x3f35bf35,0xbf6dbec4,
0x80003f80,0x3f6dbec4,0xbf35bf35,0xbec43f6d,0x3f800000,0xbec4bf6d,0xbf353f35,0x3f6d3ec4,0x8000bf80,0xbf6d3ec4,0x3f353f35,0x3ec4bf6d,
0xbf800000,0x3ec43f6d,0x3f35bf35,0xbf6dbec4,0xbf80,0xbf6d3ec4,0x3f353f35,0x3ec4bf6d,0x3f800000,0xbec4bf6d,0xbf353f35,0x3f6d3ec4,
0x3f80,0x3f6dbec4,0xbf35bf35,0xbec43f6d,0xbf800000,0x3ec43f6d,0x3f35bf35,0xbf6dbec4,0xbf80,0xbf6d3ec4,0x3f353f35,0x3ec4bf6d,
0x3f800000,0xbec4bf6d,0xbf353f35,0x3f6d3ec4,0x3f80,0x3f6dbec4,0xbf35bf35,0xbec43f6d,0xbf800000,0x3ec43f6d,0x3f35bf35,0xbf6dbec4,
0xbf800000,0x3e483f7b,0x3f6dbec4,0xbf0ebf55,0xbf353f35,0x3f553f0e,0x3ec4bf6d,0xbf7bbe48,0x8000bf80,0xbf7b3e48,0x3ec43f6d,0x3f55bf0e,
0xbf35bf35,0xbf0e3f55,0x3f6d3ec4,0x3e48bf7b,0x3f800000,0xbe48bf7b,0xbf6d3ec4,0x3f0e3f55,0x3f35bf35,0xbf55bf0e,0xbec43f6d,0x3f7b3e48,
0x80003f80,0x3f7bbe48,0xbec4bf6d,0xbf553f0e,0x3f353f35,0x3f0ebf55,0xbf6dbec4,0xbe483f7b,0x3f353f35,0x3f0ebf55,0xbf6dbec4,0xbe483f7b,
0x3f80,0x3f7bbe48,0xbec4bf6d,0xbf553f0e,0xbf353f35,0x3f553f0e,0x3ec4bf6d,0xbf7bbe48,0xbf800000,0x3e483f7b,0x3f6dbec4,0xbf0ebf55,
0xbf35bf35,0xbf0e3f55,0x3f6d3ec4,0x3e48bf7b,0xbf80,0xbf7b3e48,0x3ec43f6d,0x3f55bf0e,0x3f35bf35,0xbf55bf0e,0xbec43f6d,0x3f7b3e48,
0x3f800000,0xbe48bf7b,0xbf6d3ec4,0x3f0e3f55,0x80003f80,0x3f800000,0x8000bf80,0xbf800000,0x80003f80,0x3f800000,0x8000bf80,0xbf800000,
0x80003f80,0x3f800000,0x8000bf80,0xbf800000,0x80003f80,0x3f800000,0x8000bf80,0xbf800000,0x80003f80,0x3f800000,0x8000bf80,0xbf800000,
0x80003f80,0x3f800000,0x8000bf80,0xbf800000,0x80003f80,0x3f800000,0x8000bf80,0xbf800000,0x80003f80,0x3f800000,0x8000bf80,0xbf800000,
0x3f800000,0xbf80,0xbf800000,0x3f80,0x3f800000,0xbf80,0xbf800000,0x3f80,0x3f800000,0xbf80,0xbf800000,0x3f80,
0x3f800000,0xbf80,0xbf800000,0x3f80,0x3f800000,0xbf80,0xbf800000,0x3f80,0x3f800000,0xbf80,0xbf800000,0x3f80,
0x3f800000,0xbf80,0xbf800000,0x3f80,0x3f800000,0xbf80,0xbf800000,0x3f80,0xbf800000,0xbe483f7b,0x3f6d3ec4,0x3f0ebf55,
0xbf35bf35,0xbf553f0e,0x3ec43f6d,0x3f7bbe48,0x80003f80,0x3f7b3e48,0x3ec4bf6d,0xbf55bf0e,0xbf353f35,0x3f0e3f55,0x3f6dbec4,0xbe48bf7b,
0x3f800000,0x3e48bf7b,0xbf6dbec4,0xbf0e3f55,0x3f353f35,0x3f55bf0e,0xbec4bf6d,0xbf7b3e48,0x8000bf80,0xbf7bbe48,0xbec43f6d,0x3f553f0e,
0x3f35bf35,0xbf0ebf55,0xbf6d3ec4,0x3e483f7b,0xbf353f35,0x3f0e3f55,0x3f6dbec4,0xbe48bf7b,0x3f80,0x3f7b3e48,0x3ec4bf6d,0xbf55bf0e,
0x3f353f35,0x3f55bf0e,0xbec4bf6d,0xbf7b3e48,0x3f800000,0x3e48bf7b,0xbf6dbec4,0xbf0e3f55,0x3f35bf35,0xbf0ebf55,0xbf6d3ec4,0x3e483f7b,
0xbf80,0xbf7bbe48,0xbec43f6d,0x3f553f0e,0xbf35bf35,0xbf553f0e,0x3ec43f6d,0x3f7bbe48,0xbf800000,0xbe483f7b,0x3f6d3ec4,0x3f0ebf55,
0x80003f80,0x3f6d3ec4,0x3f35bf35,0xbec4bf6d,0xbf800000,0xbec43f6d,0x3f353f35,0x3f6dbec4,0x8000bf80,0xbf6dbec4,0xbf353f35,0x3ec43f6d,
0x3f800000,0x3ec4bf6d,0xbf35bf35,0xbf6d3ec4,0x80003f80,0x3f6d3ec4,0x3f35bf35,0xbec4bf6d,0xbf800000,0xbec43f6d,0x3f353f35,0x3f6dbec4,
0x8000bf80,0xbf6dbec4,0xbf353f35,0x3ec43f6d,0x3f800000,0x3ec4bf6d,0xbf35bf35,0xbf6d3ec4,0x3f80,0x3f6d3ec4,0x3f35bf35,0xbec4bf6d,
0x3f800000,0x3ec4bf6d,0xbf35bf35,0xbf6d3ec4,0xbf80,0xbf6dbec4,0xbf353f35,0x3ec43f6d,0xbf800000,0xbec43f6d,0x3f353f35,0x3f6dbec4,
0x3f80,0x3f6d3ec4,0x3f35bf35,0xbec4bf6d,0x3f800000,0x3ec4bf6d,0xbf35bf35,0xbf6d3ec4,0xbf80,0xbf6dbec4,0xbf353f35,0x3ec43f6d,
0xbf800000,0xbec43f6d,0x3f353f35,0x3f6dbec4,0xbf800000,0xbf0e3f55,0x3ec43f6d,0x3f7b3e48,0x3f35bf35,0xbe48bf7b,0xbf6dbec4,0xbf553f0e,
0x8000bf80,0xbf55bf0e,0xbf6d3ec4,0xbe483f7b,0x3f353f35,0x3f7bbe48,0x3ec4bf6d,0xbf0ebf55,0x3f800000,0x3f0ebf55,0xbec4bf6d,0xbf7bbe48,
0xbf353f35,0x3e483f7b,0x3f6d3ec4,0x3f55bf0e,0x80003f80,0x3f553f0e,0x3f6dbec4,0x3e48bf7b,0xbf35bf35,0xbf7b3e48,0xbec43f6d,0x3f0e3f55,
0xbf35bf35,0xbf7b3e48,0xbec43f6d,0x3f0e3f55,0x3f80,0x3f553f0e,0x3f6dbec4,0x3e48bf7b,0x3f35bf35,0xbe48bf7b,0xbf6dbec4,0xbf553f0e,
0xbf800000,0xbf0e3f55,0x3ec43f6d,0x3f7b3e48,0x3f353f35,0x3f7bbe48,0x3ec4bf6d,0xbf0ebf55,0xbf80,0xbf55bf0e,0xbf6d3ec4,0xbe483f7b,
0xbf353f35,0x3e483f7b,0x3f6d3ec4,0x3f55bf0e,0x3f800000,0x3f0ebf55,0xbec4bf6d,0xbf7bbe48,0x80003f80,0x3f353f35,0x3f800000,0x3f35bf35,
0x8000bf80,0xbf35bf35,0xbf800000,0xbf353f35,0x80003f80,0x3f353f35,0x3f800000,0x3f35bf35,0x8000bf80,0xbf35bf35,0xbf800000,0xbf353f35,
0x80003f80,0x3f353f35,0x3f800000,0x3f35bf35,0x8000bf80,0xbf35bf35,0xbf800000,0xbf353f35,0x80003f80,0x3f353f35,0x3f800000,0x3f35bf35,
0x8000bf80,0xbf35bf35,0xbf800000,0xbf353f35,0xbf800000,0xbf353f35,0x3f80,0x3f353f35,0x3f800000,0x3f35bf35,0xbf80,0xbf35bf35,
0xbf800000,0xbf353f35,0x3f80,0x3f353f35,0x3f800000,0x3f35bf35,0xbf80,0xbf35bf35,0xbf800000,0xbf353f35,0x3f80,0x3f353f35,
0x3f800000,0x3f35bf35,0xbf80,0xbf35bf35,0xbf800000,0xbf353f35,0x3f80,0x3f353f35,0x3f800000,0x3f35bf35,0xbf80,0xbf35bf35,
0xbf800000,0xbf553f0e,0xbec43f6d,0x3e483f7b,0x3f353f35,0x3f7b3e48,0x3f6dbec4,0x3f0ebf55,0x80003f80,0x3f0e3f55,0x3f6d3ec4,0x3f7bbe48,
0x3f35bf35,0x3e48bf7b,0xbec4bf6d,0xbf55bf0e,0x3f800000,0x3f55bf0e,0x3ec4bf6d,0xbe48bf7b,0xbf35bf35,0xbf7bbe48,0xbf6d3ec4,0xbf0e3f55,
0x8000bf80,0xbf0ebf55,0xbf6dbec4,0xbf7b3e48,0xbf353f35,0xbe483f7b,0x3ec43f6d,0x3f553f0e,0x3f35bf35,0x3e48bf7b,0xbec4bf6d,0xbf55bf0e,
0x3f80,0x3f0e3f55,0x3f6d3ec4,0x3f7bbe48,0xbf35bf35,0xbf7bbe48,0xbf6d3ec4,0xbf0e3f55,0x3f800000,0x3f55bf0e,0x3ec4bf6d,0xbe48bf7b,
0xbf353f35,0xbe483f7b,0x3ec43f6d,0x3f553f0e,0xbf80,0xbf0ebf55,0xbf6dbec4,0xbf7b3e48,0x3f353f35,0x3f7b3e48,0x3f6dbec4,0x3f0ebf55,
0xbf800000,0xbf553f0e,0xbec43f6d,0x3e483f7b,0x80003f80,0x3ec43f6d,0x3f353f35,0x3f6d3ec4,0x3f800000,0x3f6dbec4,0x3f35bf35,0x3ec4bf6d,
0x8000bf80,0xbec4bf6d,0xbf35bf35,0xbf6dbec4,0xbf800000,0xbf6d3ec4,0xbf353f35,0xbec43f6d,0x80003f80,0x3ec43f6d,0x3f353f35,0x3f6d3ec4,
0x3f800000,0x3f6dbec4,0x3f35bf35,0x3ec4bf6d,0x8000bf80,0xbec4bf6d,0xbf35bf35,0xbf6dbec4,0xbf800000,0xbf6d3ec4,0xbf353f35,0xbec43f6d,
0xbf80,0xbec4bf6d,0xbf35bf35,0xbf6dbec4,0x3f800000,0x3f6dbec4,0x3f35bf35,0x3ec4bf6d,0x3f80,0x3ec43f6d,0x3f353f35,0x3f6d3ec4,
0xbf800000,0xbf6d3ec4,0xbf353f35,0xbec43f6d,0xbf80,0xbec4bf6d,0xbf35bf35,0xbf6dbec4,0x3f800000,0x3f6dbec4,0x3f35bf35,0x3ec4bf6d,
0x3f80,0x3ec43f6d,0x3f353f35,0x3f6d3ec4,0xbf800000,0xbf6d3ec4,0xbf353f35,0xbec43f6d,0xbf800000,0xbf7b3e48,0xbf6d3ec4,0xbf553f0e,
0xbf353f35,0xbf0e3f55,0xbec43f6d,0xbe483f7b,0x8000bf80,0xbe48bf7b,0xbec4bf6d,0xbf0ebf55,0xbf35bf35,0xbf55bf0e,0xbf6dbec4,0xbf7bbe48,
0x3f800000,0x3f7bbe48,0x3f6dbec4,0x3f55bf0e,0x3f35bf35,0x3f0ebf55,0x3ec4bf6d,0x3e48bf7b,0x80003f80,0x3e483f7b,0x3ec43f6d,0x3f0e3f55,
0x3f353f35,0x3f553f0e,0x3f6d3ec4,0x3f7b3e48,0x3f353f35,0x3f553f0e,0x3f6d3ec4,0x3f7b3e48,0x3f80,0x3e483f7b,0x3ec43f6d,0x3f0e3f55,
0xbf353f35,0xbf0e3f55,0xbec43f6d,0xbe483f7b,0xbf800000,0xbf7b3e48,0xbf6d3ec4,0xbf553f0e,0xbf35bf35,0xbf55bf0e,0xbf6dbec4,0xbf7bbe48,
0xbf80,0xbe48bf7b,0xbec4bf6d,0xbf0ebf55,0x3f35bf35,0x3f0ebf55,0x3ec4bf6d,0x3e48bf7b,0x3f800000,0x3f7bbe48,0x3f6dbec4,0x3f55bf0e,
};
__device__ __align__(1024) const uint32_t c_T2W[4096] = {
0x3f800000,0x0,0x3f800000,0x0,0x3f800000,0x0,0x3f800000,0x0,0x3f800000,0x0,0x3f800000,0x0,
0x3f800000,0x0,0x3f800000,0x0,0x3f800000,0x0,0x3f7ffb11,0x3c490e90,0x3f7fffb1,0x3b490fc6,0x3f7ff84a,0x3c7b514b,
0x3f7ffec4,0x3bc90f88,0x3f7ff4e6,0x3c96c9b6,0x3f7ffd39,0x3c16cb58,0x3f7ff0e3,0x3cafea69,0x3f800000,0x0,0x3f7fec43,0x3cc90ab0,
0x3f7ffec4,0x3bc90f88,0x3f7fe129,0x3cfb49ba,0x3f7ffb11,0x3c490e90,0x3f7fd397,0x3d16c32c,0x3f7ff4e6,0x3c96c9b6,0x3f7fc38f,0x3d2fe007,
0x3f800000,0x0,0x3f7fd397,0x3d16c32c,0x3f7ffd39,0x3c16cb58,0x3f7fba9e,0x3d3c6dd5,0x3f7ff4e6,0x3c96c9b6,0x3f7f9c18,0x3d621469,
0x3f7fe705,0x3ce22a7a,0x3f7f7808,0x3d83db0a,0x3f800000,0x0,0x3f7fb10f,0x3d48fb30,0x3f7ffb11,0x3c490e90,0x3f7f84ab,0x3d7b2b74,
0x3f7fec43,0x3cc90ab0,0x3f7f4e6d,0x3d96a905,0x3f7fd397,0x3d16c32c,0x3f7f0e58,0x3dafb680,0x3f800000,0x0,0x3f7f84ab,0x3d7b2b74,
0x3f7ff84a,0x3c7b514b,0x3f7f3f54,0x3d9cecf9,0x3f7fe129,0x3cfb49ba,0x3f7eea9d,0x3dbc3ac3,0x3f7fba9e,0x3d3c6dd5,0x3f7e868b,0x3ddb7d37,
0x3f800000,0x0,0x3f7f4e6d,0x3d96a905,0x3f7ff4e6,0x3c96c9b6,0x3f7eea9d,0x3dbc3ac3,0x3f7fd397,0x3d16c32c,0x3f7e70b0,0x3de1bc2e,
0x3f7f9c18,0x3d621469,0x3f7de0b1,0x3e039502,0x3f800000,0x0,0x3f7f0e58,0x3dafb680,0x3f7ff0e3,0x3cafea69,0x3f7e868b,0x3ddb7d37,
0x3f7fc38f,0x3d2fe007,0x3f7de0b1,0x3e039502,0x3f7f7808,0x3d83db0a,0x3f7d1cdd,0x3e195be0,0x3f800000,0x0,0x3f7b14be,0x3e47c5c2,
0x3f7fb10f,0x3d48fb30,0x3f7853f8,0x3e78cfcc,0x3f7ec46d,0x3dc8bd36,0x3f74fa0b,0x3e94a031,0x3f7d3aac,0x3e164083,0x3f710908,0x3eac7cd4,
0x3f800000,0x0,0x3f7a7302,0x3e541501,0x3f7fa6e3,0x3d55880e,0x3f77583a,0x3e840270,0x3f7e9bc9,0x3dd53db9,0x3f73913f,0x3e9d9e78,
0x3f7cdf6c,0x3e1f917b,0x3f6f20b0,0x3eb6ccc3,0x3f800000,0x0,0x3f79c79d,0x3e605c13,0x3f7f9c18,0x3d621469,0x3f764d97,0x3e8b9507,
0x3f7e70b0,0x3de1bc2e,0x3f721352,0x3ea68f12,0x3f7c7eb0,0x3e28defc,0x3f6d1c1d,0x3ec1071e,0x3f800000,0x0,0x3f791298,0x3e6c9a7f,
0x3f7f90b1,0x3d6ea038,0x3f75341d,0x3e931f35,0x3f7e4323,0x3dee3876,0x3f708066,0x3eaf713a,0x3f7c187a,0x3e3228d4,0x3f6afb8c,0x3ecb2aae,
0x3f800000,0x0,0x3f7853f8,0x3e78cfcc,0x3f7f84ab,0x3d7b2b74,0x3f740bdd,0x3e9aa086,0x3f7e1324,0x3dfab273,0x3f6ed89e,0x3eb8442a,
0x3f7baccd,0x3e3b6ecf,0x3f68bf3c,0x3ed53641,0x3f800000,0x0,0x3f778bc5,0x3e827dc0,0x3f7f7808,0x3d83db0a,0x3f72d4eb,0x3ea21887,
0x3f7de0b1,0x3e039502,0x3f6d1c1d,0x3ec1071e,0x3f7b3bab,0x3e44b0b9,0x3f666771,0x3edf28a9,0x3f800000,0x0,0x3f76ba07,0x3e888e93,
0x3f7f6ac7,0x3d8a200a,0x3f718f57,0x3ea986c4,0x3f7dabcc,0x3e09cf86,0x3f6b4b0c,0x3ec9b953,0x3f7ac516,0x3e4dee60,0x3f63f473,0x3ee900b7,
0x3f800000,0x0,0x3f75dec6,0x3e8e9a22,0x3f7f5ce9,0x3d9064b4,0x3f703b37,0x3eb0eacb,0x3f7d7474,0x3e1008b7,0x3f696591,0x3ed25a09,
0x3f7a4910,0x3e57278f,0x3f61668a,0x3ef2bd43,0x3f800000,0x0,0x3f6c835e,0x3ec3ef15,0x3f7ec46d,0x3dc8bd36,0x3f61c598,0x3ef15aea,
0x3f7b14be,0x3e47c5c2,0x3f54db31,0x3f0e39da,0x3f74fa0b,0x3e94a031,0x3f45e403,0x3f226799,0x3f800000,0x0,0x3f6b4b0c,0x3ec9b953,
0x3f7eb069,0x3dcefdb7,0x3f5fe4e9,0x3ef840c8,0x3f7ac516,0x3e4dee60,0x3f5233c6,0x3f121eb0,0x3f74484b,0x3e9920fe,0x3f425b89,0x3f269de3,
0x3f800000,0x0,0x3f6a09a7,0x3ecf7bca,0x3f7e9bc9,0x3dd53db9,0x3f5df6be,0x3eff17b2,0x3f7a7302,0x3e541501,0x3f4f7a1f,0x3f15f6d9,
0x3f73913f,0x3e9d9e78,0x3f3ebc1b,0x3f2ac082,0x3f800000,0x0,0x3f68bf3c,0x3ed53641,0x3f7e868b,0x3ddb7d37,0x3f5bfb34,0x3f02ef9f,
0x3f7a1e84,0x3e5a3997,0x3f4cae79,0x3f19c200,0x3f72d4eb,0x3ea21887,0x3f3b0629,0x3f2ecef7,0x3f800000,0x0,0x3f676bd8,0x3edae880,
0x3f7e70b0,0x3de1bc2e,0x3f59f26a,0x3f064b82,0x3f79c79d,0x3e605c13,0x3f49d112,0x3f1d7fd1,0x3f721352,0x3ea68f12,0x3f373a23,0x3f32c8c9,
0x3f800000,0x0,0x3f660f88,0x3ee0924f,0x3f7e5a38,0x3de7fa9a,0x3f57dc7f,0x3f099f4e,0x3f796e4e,0x3e667c66,0x3f46e22a,0x3f212ff9,
0x3f714c7a,0x3eab0201,0x3f33587a,0x3f36ad7f,0x3f800000,0x0,0x3f64aa59,0x3ee63375,0x3f7e4323,0x3dee3876,0x3f55b993,0x3f0cead0,
0x3f791298,0x3e6c9a7f,0x3f43e200,0x3f24d225,0x3f708066,0x3eaf713a,0x3f2f61a5,0x3f3a7ca4,0x3f800000,0x0,0x3f633c5a,0x3eebcbbb,
0x3f7e2b72,0x3df475c0,0x3f5389c7,0x3f102dd5,0x3f78b47b,0x3e72b651,0x3f40d0da,0x3f286605,0x3f6faf1b,0x3eb3dca5,0x3f2b561b,0x3f3e35c5,
0x3f800000,0x0,0x3f54db31,0x3f0e39da,0x3f7d3aac,0x3e164083,0x3f3daef9,0x3f2beb4a,0x3f74fa0b,0x3e94a031,0x3f226799,0x3f45e403,
0x3f676bd8,0x3edae880,0x3f039c3d,0x3f5b941a,0x3f800000,0x0,0x3f531849,0x3f10d3cd,0x3f7d1cdd,0x3e195be0,0x3f3b0629,0x3f2ecef7,
0x3f748422,0x3e97a117,0x3f1ebc12,0x3f48d8b3,0x3f666771,0x3edf28a9,0x3efdbabb,0x3f5e5aa6,0x3f800000,0x0,0x3f514d3d,0x3f13682a,
0x3f7cfe73,0x3e1c76de,0x3f385216,0x3f31a81d,0x3f740bdd,0x3e9aa086,0x3f1b02c6,0x3f4bbbf8,0x3f655e0b,0x3ee363fa,0x3ef41f07,0x3f6106f2,
0x3f800000,0x0,0x3f4f7a1f,0x3f15f6d9,0x3f7cdf6c,0x3e1f917b,0x3f3592e7,0x3f34768f,0x3f73913f,0x3e9d9e78,0x3f173c07,0x3f4e8d90,
0x3f644fac,0x3ee79a5d,0x3eea6681,0x3f6398ac,0x3f800000,0x0,0x3f4d9f02,0x3f187fc0,0x3f7cbfc9,0x3e22abb6,0x3f32c8c9,0x3f373a23,
0x3f731447,0x3ea09ae5,0x3f13682a,0x3f514d3d,0x3f633c5a,0x3eebcbbb,0x3ee0924f,0x3f660f88,0x3f800000,0x0,0x3f4bbbf8,0x3f1b02c6,
0x3f7c9f8a,0x3e25c58c,0x3f2ff3e6,0x3f39f2ac,0x3f7294f8,0x3ea395c5,0x3f0f8784,0x3f53fac3,0x3f62241a,0x3eeff7fb,0x3ed6a399,0x3f686b39,
0x3f800000,0x0,0x3f49d112,0x3f1d7fd1,0x3f7c7eb0,0x3e28defc,0x3f2d1469,0x3f3ca003,0x3f721352,0x3ea68f12,0x3f0b9a6b,0x3f5695e5,
0x3f6106f2,0x3ef41f07,0x3ecc9b8b,0x3f6aab7b,0x3f800000,0x0,0x3f47de65,0x3f1ff6cb,0x3f7c5d3a,0x3e2bf804,0x3f2a2a80,0x3f3f41fc,
0x3f718f57,0x3ea986c4,0x3f07a136,0x3f591e6a,0x3f5fe4e9,0x3ef840c8,0x3ec27b55,0x3f6cd007,0x3f800000,0x0,0x3f800000,0x0,
0x3f800000,0x0,0x3f800000,0x0,0x3f800000,0x0,0x3f800000,0x0,0x3f800000,0x0,0x3f800000,0x0,
0x3f7fec43,0x3cc90ab0,0x3f7fd397,0x3d16c32c,0x3f7fe705,0x3ce22a7a,0x3f7fcbe2,0x3d2351cb,0x3f7fe129,0x3cfb49ba,0x3f7fc38f,0x3d2fe007,
0x3f7fdaaf,0x3d0a342f,0x3f7fba9e,0x3d3c6dd5,0x3f7fb10f,0x3d48fb30,0x3f7f4e6d,0x3d96a905,0x3f7f9c18,0x3d621469,0x3f7f2f9d,0x3da3308c,
0x3f7f84ab,0x3d7b2b74,0x3f7f0e58,0x3dafb680,0x3f7f6ac7,0x3d8a200a,0x3f7eea9d,0x3dbc3ac3,0x3f7f4e6d,0x3d96a905,0x3f7e70b0,0x3de1bc2e,
0x3f7f1f49,0x3da973ba,0x3f7e2b72,0x3df475c0,0x3f7eea9d,0x3dbc3ac3,0x3f7de0b1,0x3e039502,0x3f7eb069,0x3dcefdb7,0x3f7d906e,0x3e0cec4a,
0x3f7ec46d,0x3dc8bd36,0x3f7d3aac,0x3e164083,0x3f7e70b0,0x3de1bc2e,0x3f7cbfc9,0x3e22abb6,0x3f7e1324,0x3dfab273,0x3f7c3b28,0x3e2f10a2,
0x3f7dabcc,0x3e09cf86,0x3f7baccd,0x3e3b6ecf,0x3f7e1324,0x3dfab273,0x3f7baccd,0x3e3b6ecf,0x3f7d906e,0x3e0cec4a,0x3f7aed37,0x3e4ada4f,
0x3f7cfe73,0x3e1c76de,0x3f7a1e84,0x3e5a3997,0x3f7c5d3a,0x3e2bf804,0x3f7940c0,0x3e698bba,0x3f7d3aac,0x3e164083,0x3f79c79d,0x3e605c13,
0x3f7c7eb0,0x3e28defc,0x3f78b47b,0x3e72b651,0x3f7baccd,0x3e3b6ecf,0x3f778bc5,0x3e827dc0,0x3f7ac516,0x3e4dee60,0x3f764d97,0x3e8b9507,
0x3f7c3b28,0x3e2f10a2,0x3f778bc5,0x3e827dc0,0x3f7b3bab,0x3e44b0b9,0x3f76167a,0x3e8d17c0,0x3f7a1e84,0x3e5a3997,0x3f748422,0x3e97a117,
0x3f78e3d6,0x3e6fa8b2,0x3f72d4eb,0x3ea21887,0x3f6c835e,0x3ec3ef15,0x3f54db31,0x3f0e39da,0x3f676bd8,0x3edae880,0x3f4d9f02,0x3f187fc0,
0x3f61c598,0x3ef15aea,0x3f45e403,0x3f226799,0x3f5b941a,0x3f039c3d,0x3f3daef9,0x3f2beb4a,0x3f6a09a7,0x3ecf7bca,0x3f4f7a1f,0x3f15f6d9,
0x3f644fac,0x3ee79a5d,0x3f476085,0x3f209393,0x3f5df6be,0x3eff17b2,0x3f3ebc1b,0x3f2ac082,0x3f570348,0x3f0af1b7,0x3f3592e7,0x3f34768f,
0x3f676bd8,0x3edae880,0x3f49d112,0x3f1d7fd1,0x3f6106f2,0x3ef41f07,0x3f40d0da,0x3f286605,0x3f59f26a,0x3f064b82,0x3f373a23,0x3f32c8c9,
0x3f5233c6,0x3f121eb0,0x3f2d1469,0x3f3ca003,0x3f64aa59,0x3ee63375,0x3f43e200,0x3f24d225,0x3f5d924d,0x3f003a06,0x3f39f2ac,0x3f2ff3e6,
0x3f55b993,0x3f0cead0,0x3f2f61a5,0x3f3a7ca4,0x3f4d26fd,0x3f19210f,0x3f24381a,0x3f446337,0x3f61c598,0x3ef15aea,0x3f3daef9,0x3f2beb4a,
0x3f59f26a,0x3f064b82,0x3f32c8c9,0x3f373a23,0x3f514d3d,0x3f13682a,0x3f273656,0x3f41d870,0x3f47de65,0x3f1ff6cb,0x3f1b02c6,0x3f4bbbf8,
0x3f5ebe05,0x3efc5d27,0x3f373a23,0x3f32c8c9,0x3f5627fe,0x3f0c42c9,0x3f2b561b,0x3f3e35c5,0x3f4cae79,0x3f19c200,0x3f1ebc12,0x3f48d8b3,
0x3f425b89,0x3f269de3,0x3f11796b,0x3f52a649,0x3f5b941a,0x3f039c3d,0x3f3085bb,0x3f396842,0x3f5233c6,0x3f121eb0,0x3f239da9,0x3f44e3f5,
0x3f47de65,0x3f1ff6cb,0x3f15f6d9,0x3f4f7a1f,0x3f3ca003,0x3f2d1469,0x3f07a136,0x3f591e6a,0x3f584853,0x3f08f59b,0x3f299415,0x3f3fc767,
0x3f4e1689,0x3f17de12,0x3f1ba299,0x3f4b41fa,0x3f42de29,0x3f26050a,0x3f0cead0,0x3f55b993,0x3f36ad7f,0x3f33587a,0x3efafef7,0x3f5f20db,
0x3f3504f3,0x3f3504f3,0x3ec3ef15,0x3f6c835e,0x3f226799,0x3f45e403,0x3e94a031,0x3f74fa0b,0x3f0e39da,0x3f54db31,0x3e47c5c2,0x3f7b14be,
0x3ef15aea,0x3f61c598,0x3dc8bd36,0x3f7ec46d,0x3f3085bb,0x3f396842,0x3eb263ef,0x3f6ff573,0x3f1ce11f,0x3f4a4c87,0x3e80f8c0,0x3f77beb7,
0x3f07a136,0x3f591e6a,0x3e1c76de,0x3f7cfe73,0x3ee1fb6a,0x3f65b710,0x3d55880e,0x3f7fa6e3,0x3f2beb4a,0x3f3daef9,0x3ea09ae5,0x3f731447,
0x3f173c07,0x3f4e8d90,0x3e5a3997,0x3f7a1e84,0x3f00e7e4,0x3f5d2d53,0x3de1bc2e,0x3f7e70b0,0x3ed25a09,0x3f696591,0x3bc90f88,0x3f7ffec4,
0x3f273656,0x3f41d870,0x3e8e9a22,0x3f75dec6,0x3f11796b,0x3f52a649,0x3e3228d4,0x3f7c187a,0x3ef41f07,0x3f6106f2,0x3d8a200a,0x3f7f6ac7,
0x3ec27b55,0x3f6cd007,0xbd2351cb,0x3f7fcbe2,0x3f226799,0x3f45e403,0x3e78cfcc,0x3f7853f8,0x3f0b9a6b,0x3f5695e5,0x3e09cf86,0x3f7dabcc,
0x3ee63375,0x3f64aa59,0x3cc90ab0,0x3f7fec43,0x3eb263ef,0x3f6ff573,0xbdafb680,0x3f7f0e58,0x3f1d7fd1,0x3f49d112,0x3e541501,0x3f7a7302,
0x3f05a02c,0x3f5a5ba0,0x3dc27c39,0x3f7ed7d4,0x3ed8106b,0x3f6816a8,0xbc96c9b6,0x3f7ff4e6,0x3ea21887,0x3f72d4eb,0xbe06b26e,0x3f7dc68c,
0x3f187fc0,0x3f4d9f02,0x3e2f10a2,0x3f7c3b28,0x3eff17b2,0x3f5df6be,0x3d621469,0x3f7f9c18,0x3ec9b953,0x3f6b4b0c,0xbd7b2b74,0x3f7f84ab,
0x3e919ddd,0x3f756d97,0xbe354098,0x3f7bf531,0x3f13682a,0x3f514d3d,0x3e09cf86,0x3f7dabcc,0x3ef2bd43,0x3f61668a,0x3c7b514b,0x3f7ff84a,
0x3ebb31a0,0x3f6e46be,0xbdd53db9,0x3f7e9bc9,0x3e80f8c0,0x3f77beb7,0xbe636c83,0x3f799b43,0x3ec3ef15,0x3f6c835e,0xbe47c5c2,0x3f7b14be,
0x3e78cfcc,0x3f7853f8,0xbeac7cd4,0x3f710908,0x3dc8bd36,0x3f7ec46d,0xbef15aea,0x3f61c598,0xbd48fb30,0x3f7fb10f,0xbf187fc0,0x3f4d9f02,
0x3eb8442a,0x3f6ed89e,0xbe6c9a7f,0x3f791298,0x3e5d4b1a,0x3f79f35e,0xbebf926f,0x3f6d67a1,0x3d8a200a,0x3f7f6ac7,0xbf0242b1,0x3f5c61c7,
0xbda973ba,0x3f7f1f49,0xbf21cbfb,0x3f466354,0x3eac7cd4,0x3f710908,0xbe888e93,0x3f76ba07,0x3e419b37,0x3f7b61fc,0xbed25a09,0x3f696591,
0x3d16c32c,0x3f7fd397,0xbf0b9a6b,0x3f5695e5,0xbdee3876,0x3f7e4323,0xbf2ac082,0x3f3ebc1b,0x3ea09ae5,0x3f731447,0xbe9aa086,0x3f740bdd,
0x3e25c58c,0x3f7c9f8a,0xbee4cbfe,0x3f650479,0x3bc90f88,0x3f7ffec4,0xbf14b039,0x3f5064af,0xbe195be0,0x3f7d1cdd,0xbf33587a,0x3f36ad7f,
0x3e94a031,0x3f74fa0b,0xbeac7cd4,0x3f710908,0x3e09cf86,0x3f7dabcc,0xbef6e0cb,0x3f604621,0xbcc90ab0,0x3f7fec43,0xbf1d7fd1,0x3f49d112,
0xbe3b6ecf,0x3f7baccd,0xbf3b8f3b,0x3f2e3bde,0x3e888e93,0x3f76ba07,0xbebe1d4a,0x3f6db293,0x3ddb7d37,0x3f7e868b,0xbf044889,0x3f5b2c79,
0xbd621469,0x3f7f9c18,0xbf26050a,0x3f42de29,0xbe5d4b1a,0x3f79f35e,0xbf436051,0x3f256bcb,0x3e78cfcc,0x3f7853f8,0xbecf7bca,0x3f6a09a7,
0x3da3308c,0x3f7f2f9d,0xbf0cead0,0x3f55b993,0xbdafb680,0x3f7f0e58,0xbf2e3bde,0x3f3b8f3b,0xbe7ee6e1,0x3f77f110,0xbf4ac77f,0x3f1c420c,
0x3e605c13,0x3f79c79d,0xbee0924f,0x3f660f88,0x3d55880e,0x3f7fa6e3,0xbf1553b7,0x3f4fefa8,0xbdee3876,0x3f7e4323,0xbf36206c,0x3f33e7bc,
0xbe901c2c,0x3f75a67b,0xbf51c0c2,0x3f12c39a,0x3f800000,0x0,0x3f800000,0x0,0x3f800000,0x0,0x3f800000,0x0,
0x3f800000,0x0,0x3f800000,0x0,0x3f800000,0x0,0x3f800000,0x0,0x3f7fb10f,0x3d48fb30,0x3f7f84ab,0x3d7b2b74,
0x3f7fa6e3,0x3d55880e,0x3f7f7808,0x3d83db0a,0x3f7f9c18,0x3d621469,0x3f7f6ac7,0x3d8a200a,0x3f7f90b1,0x3d6ea038,0x3f7f5ce9,0x3d9064b4,
0x3f7ec46d,0x3dc8bd36,0x3f7e1324,0x3dfab273,0x3f7e9bc9,0x3dd53db9,0x3f7de0b1,0x3e039502,0x3f7e70b0,0x3de1bc2e,0x3f7dabcc,0x3e09cf86,
0x3f7e4323,0x3dee3876,0x3f7d7474,0x3e1008b7,0x3f7d3aac,0x3e164083,0x3f7baccd,0x3e3b6ecf,0x3f7cdf6c,0x3e1f917b,0x3f7b3bab,0x3e44b0b9,
0x3f7c7eb0,0x3e28defc,0x3f7ac516,0x3e4dee60,0x3f7c187a,0x3e3228d4,0x3f7a4910,0x3e57278f,0x3f7b14be,0x3e47c5c2,0x3f7853f8,0x3e78cfcc,
0x3f7a7302,0x3e541501,0x3f778bc5,0x3e827dc0,0x3f79c79d,0x3e605c13,0x3f76ba07,0x3e888e93,0x3f791298,0x3e6c9a7f,0x3f75dec6,0x3e8e9a22,
0x3f7853f8,0x3e78cfcc,0x3f740bdd,0x3e9aa086,0x3f77583a,0x3e840270,0x3f72d4eb,0x3ea21887,0x3f764d97,0x3e8b9507,0x3f718f57,0x3ea986c4,
0x3f75341d,0x3e931f35,0x3f703b37,0x3eb0eacb,0x3f74fa0b,0x3e94a031,0x3f6ed89e,0x3eb8442a,0x3f73913f,0x3e9d9e78,0x3f6d1c1d,0x3ec1071e,
0x3f721352,0x3ea68f12,0x3f6b4b0c,0x3ec9b953,0x3f708066,0x3eaf713a,0x3f696591,0x3ed25a09,0x3f710908,0x3eac7cd4,0x3f68bf3c,0x3ed53641,
0x3f6f20b0,0x3eb6ccc3,0x3f666771,0x3edf28a9,0x3f6d1c1d,0x3ec1071e,0x3f63f473,0x3ee900b7,0x3f6afb8c,0x3ecb2aae,0x3f61668a,0x3ef2bd43,
0x3f3504f3,0x3f3504f3,0x3f0e39da,0x3f54db31,0x3f2beb4a,0x3f3daef9,0x3f039c3d,0x3f5b941a,0x3f226799,0x3f45e403,0x3ef15aea,0x3f61c598,
0x3f187fc0,0x3f4d9f02,0x3edae880,0x3f676bd8,0x3f2beb4a,0x3f3daef9,0x3f00e7e4,0x3f5d2d53,0x3f21cbfb,0x3f466354,0x3eea6681,0x3f6398ac,
0x3f173c07,0x3f4e8d90,0x3ed25a09,0x3f696591,0x3f0c42c9,0x3f5627fe,0x3eb9bb1e,0x3f6e8ff8,0x3f226799,0x3f45e403,0x3ee63375,0x3f64aa59,
0x3f173c07,0x3f4e8d90,0x3ecc9b8b,0x3f6aab7b,0x3f0b9a6b,0x3f5695e5,0x3eb263ef,0x3f6ff573,0x3eff17b2,0x3f5df6be,0x3e97a117,0x3f748422,
0x3f187fc0,0x3f4d9f02,0x3ec9b953,0x3f6b4b0c,0x3f0c42c9,0x3f5627fe,0x3eadf73c,0x3f70c501,0x3eff17b2,0x3f5df6be,0x3e919ddd,0x3f756d97,
0x3ee4cbfe,0x3f650479,0x3e698bba,0x3f7940c0,0x3f0e39da,0x3f54db31,0x3eac7cd4,0x3f710908,0x3f00e7e4,0x3f5d2d53,0x3e8e9a22,0x3f75dec6,
0x3ee63375,0x3f64aa59,0x3e605c13,0x3f79c79d,0x3ec9b953,0x3f6b4b0c,0x3e22abb6,0x3f7cbfc9,0x3f039c3d,0x3f5b941a,0x3e8e9a22,0x3f75dec6,
0x3eea6681,0x3f6398ac,0x3e5d4b1a,0x3f79f35e,0x3ecc9b8b,0x3f6aab7b,0x3e1c76de,0x3f7cfe73,0x3eadf73c,0x3f70c501,0x3db5f8da,0x3f7efcc9,
0x3ef15aea,0x3f61c598,0x3e605c13,0x3f79c79d,0x3ed25a09,0x3f696591,0x3e1c76de,0x3f7cfe73,0x3eb263ef,0x3f6ff573,0x3dafb680,0x3f7f0e58,
0x3e919ddd,0x3f756d97,0x3c96c9b6,0x3f7ff4e6,0x3edae880,0x3f676bd8,0x3e22abb6,0x3f7cbfc9,0x3eb9bb1e,0x3f6e8ff8,0x3db5f8da,0x3f7efcc9,
0x3e97a117,0x3f748422,0x3c96c9b6,0x3f7ff4e6,0x3e698bba,0x3f7940c0,0xbd55880e,0x3f7fa6e3,0x0,0x3f800000,0xbec3ef15,0x3f6c835e,
0xbdc8bd36,0x3f7ec46d,0xbef15aea,0x3f61c598,0xbe47c5c2,0x3f7b14be,0xbf0e39da,0x3f54db31,0xbe94a031,0x3f74fa0b,0xbf226799,0x3f45e403,
0xbd48fb30,0x3f7fb10f,0xbee0924f,0x3f660f88,0xbe195be0,0x3f7d1cdd,0xbf06f686,0x3f5988ad,0xbe7ee6e1,0x3f77f110,0xbf1c420c,0x3f4ac77f,
0xbeb0eacb,0x3f703b37,0xbf2ff3e6,0x3f39f2ac,0xbdc8bd36,0x3f7ec46d,0xbefc5d27,0x3f5ebe05,0xbe4dee60,0x3f7ac516,0xbf14b039,0x3f5064af,
0xbe9aa086,0x3f740bdd,0xbf299415,0x3f3fc767,0xbecc9b8b,0x3f6aab7b,0xbf3ca003,0x3f2d1469,0xbe164083,0x3f7d3aac,0xbf0b9a6b,0x3f5695e5,
0xbe80f8c0,0x3f77beb7,0xbf21cbfb,0x3f466354,0xbeb554ec,0x3f6f6830,0xbf36206c,0x3f33e7bc,0xbee79a5d,0x3f644fac,0xbf485bca,0x3f1f599f,
0xbe47c5c2,0x3f7b14be,0xbf187fc0,0x3f4d9f02,0xbe9aa086,0x3f740bdd,0xbf2e3bde,0x3f3b8f3b,0xbecf7bca,0x3f6a09a7,0xbf41d870,0x3f273656,
0xbf00e7e4,0x3f5d2d53,0xbf531849,0x3f10d3cd,0xbe78cfcc,0x3f7853f8,0xbf24d225,0x3f43e200,0xbeb3dca5,0x3f6faf1b,0xbf39f2ac,0x3f2ff3e6,
0xbee900b7,0x3f63f473,0xbf4cae79,0x3f19c200,0xbf0d9281,0x3f554aa4,0xbf5cc7d1,0x3f019573,0xbe94a031,0x3f74fa0b,0xbf3085bb,0x3f396842,
0xbecc9b8b,0x3f6aab7b,0xbf44e3f5,0x3f239da9,0xbf00e7e4,0x3f5d2d53,0xbf5695e5,0x3f0b9a6b,0xbf19c200,0x3f4cae79,0xbf655e0b,0x3ee363fa,
0xbeac7cd4,0x3f710908,0xbf3b8f3b,0x3f2e3bde,0xbee4cbfe,0x3f650479,0xbf4f0417,0x3f16999f,0xbf0cead0,0x3f55b993,0xbf5f8327,0x3ef9a02d,
0xbf256bcb,0x3f436051,0xbf6cd007,0x3ec27b55,0xbf3504f3,0x3f3504f3,0xbf7b14be,0x3e47c5c2,0xbf4d9f02,0x3f187fc0,0xbf7fb10f,0x3d48fb30,
0xbf61c598,0x3ef15aea,0xbf7ec46d,0xbdc8bd36,0xbf710908,0x3eac7cd4,0xbf7853f8,0xbe78cfcc,0xbf3daef9,0x3f2beb4a,0xbf7dabcc,0x3e09cf86,
0xbf554aa4,0x3f0d9281,0xbf7ff84a,0xbc7b514b,0xbf6816a8,0x3ed8106b,0xbf7c7eb0,0xbe28defc,0xbf75a67b,0x3e901c2c,0xbf73530e,0xbe9f1cdf,
0xbf45e403,0x3f226799,0xbf7f4e6d,0x3d96a905,0xbf5c61c7,0x3f0242b1,0xbf7f2f9d,0xbda3308c,0xbf6db293,0x3ebe1d4a,0xbf791298,0xbe6c9a7f,
0xbf796e4e,0x3e667c66,0xbf6d1c1d,0xbec1071e,0xbf4d9f02,0x3f187fc0,0xbf7ffb11,0x3c490e90,0xbf62df7b,0x3eed3063,0xbf7d57de,0xbe1324ca,
0xbf7294f8,0x3ea395c5,0xbf748422,0xbe97a117,0xbf7c5d3a,0x3e2bf804,0xbf65b710,0xbee1fb6a,0xbf54db31,0x3f0e39da,0xbf7fb10f,0xbd48fb30,
0xbf68bf3c,0x3ed53641,0xbf7a7302,0xbe541501,0xbf76ba07,0x3e888e93,0xbf6ed89e,0xbeb8442a,0xbf7e70b0,0x3de1bc2e,0xbf5d2d53,0xbf00e7e4,
0xbf5b941a,0x3f039c3d,0xbf7e70b0,0xbde1bc2e,0xbf6dfcf2,0x3ebca7af,0xbf76841b,0xbe8a11f7,0xbf7a1e84,0x3e5a3997,0xbf6816a8,0xbed8106b,
0xbf7fa6e3,0x3d55880e,0xbf5389c7,0xbf102dd5,0xbf61c598,0x3ef15aea,0xbf7c3b28,0xbe2f10a2,0xbf7294f8,0x3ea395c5,0xbf718f57,0xbea986c4,
0xbf7cbfc9,0x3e22abb6,0xbf604621,0xbef6e0cb,0xbf7ffec4,0xbbc90f88,0xbf48d8b3,0xbf1ebc12,0xbf676bd8,0x3edae880,0xbf791298,0xbe6c9a7f,
0xbf76841b,0x3e8a11f7,0xbf6b99fb,0xbec8477c,0xbf7e9bc9,0x3dd53db9,0xbf577026,0xbf0a48ad,0xbf7f7808,0xbd83db0a,0xbf3d27b8,0xbf2c800f,
0x3f800000,0x0,0x3f800000,0x0,0x3f800000,0x0,0x3f800000,0x0,0x3f800000,0x0,0x3f800000,0x0,
0x3f800000,0x0,0x3f800000,0x0,0x3f7f4e6d,0x3d96a905,0x3f7f0e58,0x3dafb680,0x3f7f3f54,0x3d9cecf9,0x3f7efcc9,0x3db5f8da,
0x3f7f2f9d,0x3da3308c,0x3f7eea9d,0x3dbc3ac3,0x3f7f1f49,0x3da973ba,0x3f7ed7d4,0x3dc27c39,0x3f7d3aac,0x3e164083,0x3f7c3b28,0x3e2f10a2,
0x3f7cfe73,0x3e1c76de,0x3f7bf531,0x3e354098,0x3f7cbfc9,0x3e22abb6,0x3f7baccd,0x3e3b6ecf,0x3f7c7eb0,0x3e28defc,0x3f7b61fc,0x3e419b37,
0x3f79c79d,0x3e605c13,0x3f778bc5,0x3e827dc0,0x3f7940c0,0x3e698bba,0x3f76ef5b,0x3e870ada,0x3f78b47b,0x3e72b651,0x3f764d97,0x3e8b9507,
0x3f7822d1,0x3e7bdba4,0x3f75a67b,0x3e901c2c,0x3f74fa0b,0x3e94a031,0x3f710908,0x3eac7cd4,0x3f740bdd,0x3e9aa086,0x3f6ff573,0x3eb263ef,
0x3f731447,0x3ea09ae5,0x3f6ed89e,0x3eb8442a,0x3f721352,0x3ea68f12,0x3f6db293,0x3ebe1d4a,0x3f6ed89e,0x3eb8442a,0x3f68bf3c,0x3ed53641,
0x3f6d67a1,0x3ebf926f,0x3f671599,0x3edc53c1,0x3f6be858,0x3ec6d529,0x3f655e0b,0x3ee363fa,0x3f6a5ad9,0x3ece0bea,0x3f6398ac,0x3eea6681,
0x3f676bd8,0x3edae880,0x3f5ebe05,0x3efc5d27,0x3f655e0b,0x3ee363fa,0x3f5c61c7,0x3f0242b1,0x3f633c5a,0x3eebcbbb,0x3f59f26a,0x3f064b82,
0x3f6106f2,0x3ef41f07,0x3f577026,0x3f0a48ad,0x3f5ebe05,0x3efc5d27,0x3f531849,0x3f10d3cd,0x3f5bfb34,0x3f02ef9f,0x3f4fefa8,0x3f1553b7,
0x3f591e6a,0x3f07a136,0x3f4cae79,0x3f19c200,0x3f5627fe,0x3f0c42c9,0x3f495521,0x3f1e1e22,0x3ec3ef15,0x3f6c835e,0x3e47c5c2,0x3f7b14be,
0x3eac7cd4,0x3f710908,0x3e164083,0x3f7d3aac,0x3e94a031,0x3f74fa0b,0x3dc8bd36,0x3f7ec46d,0x3e78cfcc,0x3f7853f8,0x3d48fb30,0x3f7fb10f,
0x3ea09ae5,0x3f731447,0x3de1bc2e,0x3f7e70b0,0x3e870ada,0x3f76ef5b,0x3d6ea038,0x3f7f90b1,0x3e5a3997,0x3f7a1e84,0x3bc90f88,0x3f7ffec4,
0x3e25c58c,0x3f7c9f8a,0xbd3c6dd5,0x3f7fba9e,0x3e78cfcc,0x3f7853f8,0x3cc90ab0,0x3f7fec43,0x3e419b37,0x3f7b61fc,0xbcfb49ba,0x3f7fe129,
0x3e09cf86,0x3f7dabcc,0xbdafb680,0x3f7f0e58,0x3da3308c,0x3f7f2f9d,0xbe1008b7,0x3f7d7474,0x3e2f10a2,0x3f7c3b28,0xbd7b2b74,0x3f7f84ab,
0x3de7fa9a,0x3f7e5a38,0xbdf475c0,0x3f7e2b72,0x3d621469,0x3f7f9c18,0xbe354098,0x3f7bf531,0xbb490fc6,0x3f7fffb1,0xbe6fa8b2,0x3f78e3d6,
0x3dc8bd36,0x3f7ec46d,0xbe164083,0x3f7d3aac,0x3d16c32c,0x3f7fd397,0xbe541501,0x3f7a7302,0xbcc90ab0,0x3f7fec43,0xbe888e93,0x3f76ba07,
0xbdafb680,0x3f7f0e58,0xbea68f12,0x3f721352,0x3cc90ab0,0x3f7fec43,0xbe6c9a7f,0x3f791298,0xbd2351cb,0x3f7fcbe2,0xbe9620d2,0x3f74bf62,
0xbdd53db9,0x3f7e9bc9,0xbeb554ec,0x3f6f6830,0xbe2bf804,0x3f7c5d3a,0xbed3c867,0x3f6912ae,0xbd48fb30,0x3f7fb10f,0xbea09ae5,0x3f731447,
0xbdee3876,0x3f7e4323,0xbec1071e,0x3f6d1c1d,0xbe3b6ecf,0x3f7baccd,0xbee0924f,0x3f660f88,0xbe7ee6e1,0x3f77f110,0xbeff17b2,0x3f5df6be,
0xbdfab273,0x3f7e1324,0xbec9b953,0x3f6b4b0c,0xbe44b0b9,0x3f7b3bab,0xbeea6681,0x3f6398ac,0xbe8586ce,0x3f772417,0xbf04f484,0x3f5ac450,
0xbea80b1f,0x3f71d19f,0xbf140c5f,0x3f50d937,0xbf3504f3,0x3f3504f3,0xbf6c835e,0x3ec3ef15,0xbf45e403,0x3f226799,0xbf74fa0b,0x3e94a031,
0xbf54db31,0x3f0e39da,0xbf7b14be,0x3e47c5c2,0xbf61c598,0x3ef15aea,0xbf7ec46d,0x3dc8bd36,0xbf41d870,0x3f273656,0xbf740bdd,0x3e9aa086,
0xbf51c0c2,0x3f12c39a,0xbf7a9c59,0x3e5101f1,0xbf5f8327,0x3ef9a02d,0xbf7e9bc9,0x3dd53db9,0xbf6afb8c,0x3ecb2aae,0xbf7fffb1,0x3b490fc6,
0xbf4d9f02,0x3f187fc0,0xbf79c79d,0x3e605c13,0xbf5c61c7,0x3f0242b1,0xbf7e4323,0x3dee3876,0xbf68bf3c,0x3ed53641,0xbf7ffb11,0x3c490e90,
0xbf7294f8,0x3ea395c5,0xbf7eea9d,0xbdbc3ac3,0xbf584853,0x3f08f59b,0xbf7dabcc,0x3e09cf86,0xbf65b710,0x3ee1fb6a,0xbf7fe705,0x3ce22a7a,
0xbf708066,0x3eaf713a,0xbf7f2f9d,0xbda3308c,0xbf788486,0x3e75c35a,0xbf7b87b2,0xbe3e853e,0xbf61c598,0x3ef15aea,0xbf7fb10f,0x3d48fb30,
0xbf6db293,0x3ebe1d4a,0xbf7f84ab,0xbd7b2b74,0xbf76ba07,0x3e888e93,0xbf7c3b28,0xbe2f10a2,0xbf7cbfc9,0x3e22abb6,0xbf75dec6,0xbe8e9a22,
0xbf6a09a7,0x3ecf7bca,0xbf7fd397,0xbd16c32c,0xbf74484b,0x3e9920fe,0xbf7d1cdd,0xbe195be0,0xbf7b61fc,0x3e419b37,0xbf772417,0xbe8586ce,
0xbf7f3f54,0x3d9cecf9,0xbf6dfcf2,0xbebca7af,0xbf710908,0x3eac7cd4,0xbf7e1324,0xbdfab273,0xbf796e4e,0x3e667c66,0xbf78b47b,0xbe72b651,
0xbf7e70b0,0x3de1bc2e,0xbf6ff573,0xbeb263ef,0xbf7ffec4,0xbbc90f88,0xbf63f473,0xbee900b7,0xbf76ba07,0x3e888e93,0xbf7a7302,0xbe541501,
0xbf7d1cdd,0x3e195be0,0xbf725470,0xbea5129f,0xbf7fe129,0x3cfb49ba,0xbf66becc,0xbeddbe79,0xbf7efcc9,0xbdb5f8da,0xbf57dc7f,0xbf099f4e,
0xbf6c835e,0xbec3ef15,0xbf0e39da,0xbf54db31,0xbf5b941a,0xbf039c3d,0xbedae880,0xbf676bd8,0xbf45e403,0xbf226799,0xbe94a031,0xbf74fa0b,
0xbf2beb4a,0xbf3daef9,0xbe164083,0xbf7d3aac,0xbf64aa59,0xbee63375,0xbef6e0cb,0xbf604621,0xbf50d937,0xbf140c5f,0xbeb0eacb,0xbf703b37,
0xbf385216,0xbf31a81d,0xbe4dee60,0xbf7ac516,0xbf1ba299,0xbf4b41fa,0xbd55880e,0xbf7fa6e3,0xbf5b941a,0xbf039c3d,0xbecf7bca,0xbf6a09a7,
0xbf44e3f5,0xbf239da9,0xbe8586ce,0xbf772417,0xbf299415,0xbf3fc767,0xbde1bc2e,0xbf7e70b0,0xbf0a48ad,0xbf577026,0x3d2fe007,0xbf7fc38f,
0xbf514d3d,0xbf13682a,0xbea68f12,0xbf721352,0xbf37c655,0xbf3238aa,0xbe3228d4,0xbf7c187a,0xbf19c200,0xbf4cae79,0xbc96c9b6,0xbf7ff4e6,
0xbeeff7fb,0xbf62241a,0x3e0cec4a,0xbf7d906e,0xbf45e403,0xbf226799,0xbe78cfcc,0xbf7853f8,0xbf299415,0xbf3fc767,0xbdafb680,0xbf7f0e58,
0xbf08f59b,0xbf584853,0x3d96a905,0xbf7f4e6d,0xbec9b953,0xbf6b4b0c,0x3e6c9a7f,0xbf791298,0xbf396842,0xbf3085bb,0xbe22abb6,0xbf7cbfc9,
0xbf1a6293,0xbf4c3578,0x3b490fc6,0xbf7fffb1,0xbeee9479,0xbf628210,0x3e28defc,0xbf7c7eb0,0xbea21887,0xbf72d4eb,0x3ea5129f,0xbf725470,
0xbf2beb4a,0xbf3daef9,0xbd96a905,0xbf7f4e6d,0xbf0a48ad,0xbf577026,0x3dbc3ac3,0xbf7eea9d,0xbec9b953,0xbf6b4b0c,0x3e827dc0,0xbf778bc5,
0xbe72b651,0xbf78b47b,0x3ed25a09,0xbf696591,0xbf1d7fd1,0xbf49d112,0x3c490e90,0xbf7ffb11,0xbef2bd43,0xbf61668a,0x3e3857ec,0xbf7bd14d,
0xbea395c5,0xbf7294f8,0x3eaf713a,0xbf708066,0xbe1f917b,0xbf7cdf6c,0x3efdbabb,0xbf5e5aa6,0x3f800000,0x0,0x3f7ec46d,0x3dc8bd36,
0x3f7fec43,0x3cc90ab0,0x3f7e1324,0x3dfab273,0x3f7fb10f,0x3d48fb30,0x3f7d3aac,0x3e164083,0x3f7f4e6d,0x3d96a905,0x3f7c3b28,0x3e2f10a2,
0x3f800000,0x0,0x3f7e70b0,0x3de1bc2e,0x3f7fe705,0x3ce22a7a,0x3f7d906e,0x3e0cec4a,0x3f7f9c18,0x3d621469,0x3f7c7eb0,0x3e28defc,
0x3f7f1f49,0x3da973ba,0x3f7b3bab,0x3e44b0b9,0x3f800000,0x0,0x3f7e1324,0x3dfab273,0x3f7fe129,0x3cfb49ba,0x3f7cfe73,0x3e1c76de,
0x3f7f84ab,0x3d7b2b74,0x3f7baccd,0x3e3b6ecf,0x3f7eea9d,0x3dbc3ac3,0x3f7a1e84,0x3e5a3997,0x3f800000,0x0,0x3f7dabcc,0x3e09cf86,
0x3f7fdaaf,0x3d0a342f,0x3f7c5d3a,0x3e2bf804,0x3f7f6ac7,0x3d8a200a,0x3f7ac516,0x3e4dee60,0x3f7eb069,0x3dcefdb7,0x3f78e3d6,0x3e6fa8b2,
0x3f800000,0x0,0x3f7d3aac,0x3e164083,0x3f7fd397,0x3d16c32c,0x3f7baccd,0x3e3b6ecf,0x3f7f4e6d,0x3d96a905,0x3f79c79d,0x3e605c13,
0x3f7e70b0,0x3de1bc2e,0x3f778bc5,0x3e827dc0,0x3f800000,0x0,0x3f7cbfc9,0x3e22abb6,0x3f7fcbe2,0x3d2351cb,0x3f7aed37,0x3e4ada4f,
0x3f7f2f9d,0x3da3308c,0x3f78b47b,0x3e72b651,0x3f7e2b72,0x3df475c0,0x3f76167a,0x3e8d17c0,0x3f800000,0x0,0x3f7c3b28,0x3e2f10a2,
0x3f7fc38f,0x3d2fe007,0x3f7a1e84,0x3e5a3997,0x3f7f0e58,0x3dafb680,0x3f778bc5,0x3e827dc0,0x3f7de0b1,0x3e039502,0x3f748422,0x3e97a117,
0x3f800000,0x0,0x3f7baccd,0x3e3b6ecf,0x3f7fba9e,0x3d3c6dd5,0x3f7940c0,0x3e698bba,0x3f7eea9d,0x3dbc3ac3,0x3f764d97,0x3e8b9507,
0x3f7d906e,0x3e0cec4a,0x3f72d4eb,0x3ea21887,0x3f800000,0x0,0x3f74fa0b,0x3e94a031,0x3f7f4e6d,0x3d96a905,0x3f6ed89e,0x3eb8442a,
0x3f7d3aac,0x3e164083,0x3f676bd8,0x3edae880,0x3f79c79d,0x3e605c13,0x3f5ebe05,0x3efc5d27,0x3f800000,0x0,0x3f740bdd,0x3e9aa086,
0x3f7f3f54,0x3d9cecf9,0x3f6d67a1,0x3ebf926f,0x3f7cfe73,0x3e1c76de,0x3f655e0b,0x3ee363fa,0x3f7940c0,0x3e698bba,0x3f5bfb34,0x3f02ef9f,
0x3f800000,0x0,0x3f731447,0x3ea09ae5,0x3f7f2f9d,0x3da3308c,0x3f6be858,0x3ec6d529,0x3f7cbfc9,0x3e22abb6,0x3f633c5a,0x3eebcbbb,
0x3f78b47b,0x3e72b651,0x3f591e6a,0x3f07a136,0x3f800000,0x0,0x3f721352,0x3ea68f12,0x3f7f1f49,0x3da973ba,0x3f6a5ad9,0x3ece0bea,
0x3f7c7eb0,0x3e28defc,0x3f6106f2,0x3ef41f07,0x3f7822d1,0x3e7bdba4,0x3f5627fe,0x3f0c42c9,0x3f800000,0x0,0x3f710908,0x3eac7cd4,
0x3f7f0e58,0x3dafb680,0x3f68bf3c,0x3ed53641,0x3f7c3b28,0x3e2f10a2,0x3f5ebe05,0x3efc5d27,0x3f778bc5,0x3e827dc0,0x3f531849,0x3f10d3cd,
0x3f800000,0x0,0x3f6ff573,0x3eb263ef,0x3f7efcc9,0x3db5f8da,0x3f671599,0x3edc53c1,0x3f7bf531,0x3e354098,0x3f5c61c7,0x3f0242b1,
0x3f76ef5b,0x3e870ada,0x3f4fefa8,0x3f1553b7,0x3f800000,0x0,0x3f6ed89e,0x3eb8442a,0x3f7eea9d,0x3dbc3ac3,0x3f655e0b,0x3ee363fa,
0x3f7baccd,0x3e3b6ecf,0x3f59f26a,0x3f064b82,0x3f764d97,0x3e8b9507,0x3f4cae79,0x3f19c200,0x3f800000,0x0,0x3f6db293,0x3ebe1d4a,
0x3f7ed7d4,0x3dc27c39,0x3f6398ac,0x3eea6681,0x3f7b61fc,0x3e419b37,0x3f577026,0x3f0a48ad,0x3f75a67b,0x3e901c2c,0x3f495521,0x3f1e1e22,
0x3f800000,0x0,0x3f61c598,0x3ef15aea,0x3f7e1324,0x3dfab273,0x3f514d3d,0x3f13682a,0x3f7853f8,0x3e78cfcc,0x3f3daef9,0x3f2beb4a,
0x3f6ed89e,0x3eb8442a,0x3f273656,0x3f41d870,0x3f800000,0x0,0x3f604621,0x3ef6e0cb,0x3f7dfa38,0x3e007745,0x3f4f0417,0x3f16999f,
0x3f77f110,0x3e7ee6e1,0x3f3a7ca4,0x3f2f61a5,0x3f6dfcf2,0x3ebca7af,0x3f2302d3,0x3f456439,0x3f800000,0x0,0x3f5ebe05,0x3efc5d27,
0x3f7de0b1,0x3e039502,0x3f4cae79,0x3f19c200,0x3f778bc5,0x3e827dc0,0x3f373a23,0x3f32c8c9,0x3f6d1c1d,0x3ec1071e,0x3f1ebc12,0x3f48d8b3,
0x3f800000,0x0,0x3f5d2d53,0x3f00e7e4,0x3f7dc68c,0x3e06b26e,0x3f4a4c87,0x3f1ce11f,0x3f772417,0x3e8586ce,0x3f33e7bc,0x3f36206c,
0x3f6c3624,0x3ec5625c,0x3f1a6293,0x3f4c3578,0x3f800000,0x0,0x3f5b941a,0x3f039c3d,0x3f7dabcc,0x3e09cf86,0x3f47de65,0x3f1ff6cb,
0x3f76ba07,0x3e888e93,0x3f3085bb,0x3f396842,0x3f6b4b0c,0x3ec9b953,0x3f15f6d9,0x3f4f7a1f,0x3f800000,0x0,0x3f59f26a,0x3f064b82,
0x3f7d906e,0x3e0cec4a,0x3f456439,0x3f2302d3,0x3f764d97,0x3e8b9507,0x3f2d1469,0x3f3ca003,0x3f6a5ad9,0x3ece0bea,0x3f11796b,0x3f52a649,
0x3f800000,0x0,0x3f584853,0x3f08f59b,0x3f7d7474,0x3e1008b7,0x3f42de29,0x3f26050a,0x3f75dec6,0x3e8e9a22,0x3f299415,0x3f3fc767,
0x3f696591,0x3ed25a09,0x3f0cead0,0x3f55b993,0x3f800000,0x0,0x3f5695e5,0x3f0b9a6b,0x3f7d57de,0x3e1324ca,0x3f404c5c,0x3f28fd41,
0x3f756d97,0x3e919ddd,0x3f26050a,0x3f42de29,0x3f686b39,0x3ed6a399,0x3f084b92,0x3f58b3a1,0x3f800000,0x0,0x3f45e403,0x3f226799,
0x3f7c3b28,0x3e2f10a2,0x3f273656,0x3f41d870,0x3f710908,0x3eac7cd4,0x3f039c3d,0x3f5b941a,0x3f5ebe05,0x3efc5d27,0x3eb8442a,0x3f6ed89e,
0x3f800000,0x0,0x3f43e200,0x3f24d225,0x3f7c187a,0x3e3228d4,0x3f24381a,0x3f446337,0x3f708066,0x3eaf713a,0x3eff17b2,0x3f5df6be,
0x3f5d924d,0x3f003a06,0x3eadf73c,0x3f70c501,0x3f800000,0x0,0x3f41d870,0x3f273656,0x3f7bf531,0x3e354098,0x3f212ff9,0x3f46e22a,
0x3f6ff573,0x3eb263ef,0x3ef6e0cb,0x3f604621,0x3f5c61c7,0x3f0242b1,0x3ea395c5,0x3f7294f8,0x3f800000,0x0,0x3f3fc767,0x3f299415,
0x3f7bd14d,0x3e3857ec,0x3f1e1e22,0x3f495521,0x3f6f6830,0x3eb554ec,0x3eee9479,0x3f628210,0x3f5b2c79,0x3f044889,0x3e9920fe,0x3f74484b,
0x3f800000,0x0,0x3f3daef9,0x3f2beb4a,0x3f7baccd,0x3e3b6ecf,0x3f1b02c6,0x3f4bbbf8,0x3f6ed89e,0x3eb8442a,0x3ee63375,0x3f64aa59,
0x3f59f26a,0x3f064b82,0x3e8e9a22,0x3f75dec6,0x3f800000,0x0,0x3f3b8f3b,0x3f2e3bde,0x3f7b87b2,0x3e3e853e,0x3f17de12,0x3f4e1689,
0x3f6e46be,0x3ebb31a0,0x3eddbe79,0x3f66becc,0x3f58b3a1,0x3f084b92,0x3e840270,0x3f77583a,0x3f800000,0x0,0x3f396842,0x3f3085bb,
0x3f7b61fc,0x3e419b37,0x3f14b039,0x3f5064af,0x3f6db293,0x3ebe1d4a,0x3ed53641,0x3f68bf3c,0x3f577026,0x3f0a48ad,0x3e72b651,0x3f78b47b,
0x3f800000,0x0,0x3f373a23,0x3f32c8c9,0x3f7b3bab,0x3e44b0b9,0x3f11796b,0x3f52a649,0x3f6d1c1d,0x3ec1071e,0x3ecc9b8b,0x3f6aab7b,
0x3f5627fe,0x3f0c42c9,0x3e5d4b1a,0x3f79f35e,0x3f7b14be,0x3e47c5c2,0x3f74fa0b,0x3e94a031,0x3f79c79d,0x3e605c13,0x3f731447,0x3ea09ae5,
0x3f7853f8,0x3e78cfcc,0x3f710908,0x3eac7cd4,0x3f76ba07,0x3e888e93,0x3f6ed89e,0x3eb8442a,0x3f79c79d,0x3e605c13,0x3f721352,0x3ea68f12,
0x3f7822d1,0x3e7bdba4,0x3f6faf1b,0x3eb3dca5,0x3f764d97,0x3e8b9507,0x3f6d1c1d,0x3ec1071e,0x3f74484b,0x3e9920fe,0x3f6a5ad9,0x3ece0bea,
0x3f7853f8,0x3e78cfcc,0x3f6ed89e,0x3eb8442a,0x3f764d97,0x3e8b9507,0x3f6be858,0x3ec6d529,0x3f740bdd,0x3e9aa086,0x3f68bf3c,0x3ed53641,
0x3f718f57,0x3ea986c4,0x3f655e0b,0x3ee363fa,0x3f76ba07,0x3e888e93,0x3f6b4b0c,0x3ec9b953,0x3f74484b,0x3e9920fe,0x3f67c187,0x3ed97cb9,
0x3f718f57,0x3ea986c4,0x3f63f473,0x3ee900b7,0x3f6e8ff8,0x3eb9bb1e,0x3f5fe4e9,0x3ef840c8,0x3f74fa0b,0x3e94a031,0x3f676bd8,0x3edae880,
0x3f721352,0x3ea68f12,0x3f633c5a,0x3eebcbbb,0x3f6ed89e,0x3eb8442a,0x3f5ebe05,0x3efc5d27,0x3f6b4b0c,0x3ec9b953,0x3f59f26a,0x3f064b82,
0x3f731447,0x3ea09ae5,0x3f633c5a,0x3eebcbbb,0x3f6faf1b,0x3eb3dca5,0x3f5e5aa6,0x3efdbabb,0x3f6be858,0x3ec6d529,0x3f591e6a,0x3f07a136,
0x3f67c187,0x3ed97cb9,0x3f5389c7,0x3f102dd5,0x3f710908,0x3eac7cd4,0x3f5ebe05,0x3efc5d27,0x3f6d1c1d,0x3ec1071e,0x3f591e6a,0x3f07a136,
0x3f68bf3c,0x3ed53641,0x3f531849,0x3f10d3cd,0x3f63f473,0x3ee900b7,0x3f4cae79,0x3f19c200,0x3f6ed89e,0x3eb8442a,0x3f59f26a,0x3f064b82,
0x3f6a5ad9,0x3ece0bea,0x3f5389c7,0x3f102dd5,0x3f655e0b,0x3ee363fa,0x3f4cae79,0x3f19c200,0x3f5fe4e9,0x3ef840c8,0x3f456439,0x3f2302d3,
0x3f54db31,0x3f0e39da,0x3f226799,0x3f45e403,0x3f49d112,0x3f1d7fd1,0x3f13682a,0x3f514d3d,0x3f3daef9,0x3f2beb4a,0x3f039c3d,0x3f5b941a,
0x3f3085bb,0x3f396842,0x3ee63375,0x3f64aa59,0x3f514d3d,0x3f13682a,0x3f1b02c6,0x3f4bbbf8,0x3f456439,0x3f2302d3,0x3f0af1b7,0x3f570348,
0x3f385216,0x3f31a81d,0x3ef41f07,0x3f6106f2,0x3f2a2a80,0x3f3f41fc,0x3ed0eb2a,0x3f69b7e4,0x3f4d9f02,0x3f187fc0,0x3f13682a,0x3f514d3d,
0x3f40d0da,0x3f286605,0x3f0242b1,0x3f5c61c7,0x3f32c8c9,0x3f373a23,0x3ee0924f,0x3f660f88,0x3f239da9,0x3f44e3f5,0x3ebb31a0,0x3f6e46be,
0x3f49d112,0x3f1d7fd1,0x3f0b9a6b,0x3f5695e5,0x3f3c17d9,0x3f2da859,0x3ef2bd43,0x3f61668a,0x3f2d1469,0x3f3ca003,0x3ecc9b8b,0x3f6aab7b,
0x3f1ce11f,0x3f4a4c87,0x3ea5129f,0x3f725470,0x3f45e403,0x3f226799,0x3f039c3d,0x3f5b941a,0x3f373a23,0x3f32c8c9,0x3ee0924f,0x3f660f88,
0x3f273656,0x3f41d870,0x3eb8442a,0x3f6ed89e,0x3f15f6d9,0x3f4f7a1f,0x3e8e9a22,0x3f75dec6,0x3f41d870,0x3f273656,0x3ef6e0cb,0x3f604621,
0x3f3238aa,0x3f37c655,0x3ece0bea,0x3f6a5ad9,0x3f212ff9,0x3f46e22a,0x3ea395c5,0x3f7294f8,0x3f0ee0db,0x3f546b3b,0x3e6fa8b2,0x3f78e3d6,
0x3f3daef9,0x3f2beb4a,0x3ee63375,0x3f64aa59,0x3f2d1469,0x3f3ca003,0x3ebb31a0,0x3f6e46be,0x3f1b02c6,0x3f4bbbf8,0x3e8e9a22,0x3f75dec6,
0x3f07a136,0x3f591e6a,0x3e419b37,0x3f7b61fc,0x3f396842,0x3f3085bb,0x3ed53641,0x3f68bf3c,0x3f27ce61,0x3f4154e1,0x3ea80b1f,0x3f71d19f,
0x3f14b039,0x3f5064af,0x3e72b651,0x3f78b47b,0x3f003a06,0x3f5d924d,0x3e1324ca,0x3f7d57de,0x3f0e39da,0x3f54db31,0x3dc8bd36,0x3f7ec46d,
0x3ee63375,0x3f64aa59,0xbcc90ab0,0x3f7fec43,0x3eac7cd4,0x3f710908,0xbe164083,0x3f7d3aac,0x3e605c13,0x3f79c79d,0xbe888e93,0x3f76ba07,
0x3f08f59b,0x3f584853,0x3d7b2b74,0x3f7f84ab,0x3ed97cb9,0x3f67c187,0xbd83db0a,0x3f7f7808,0x3e9d9e78,0x3f73913f,0xbe419b37,0x3f7b61fc,
0x3e3e853e,0x3f7b87b2,0xbe9f1cdf,0x3f73530e,0x3f039c3d,0x3f5b941a,0x3cc90ab0,0x3f7fec43,0x3ecc9b8b,0x3f6aab7b,0xbdd53db9,0x3f7e9bc9,
0x3e8e9a22,0x3f75dec6,0xbe6c9a7f,0x3f791298,0x3e1c76de,0x3f7cfe73,0xbeb554ec,0x3f6f6830,0x3efc5d27,0x3f5ebe05,0xbc490e90,0x3f7ffb11,
0x3ebf926f,0x3f6d67a1,0xbe1324ca,0x3f7d57de,0x3e7ee6e1,0x3f77f110,0xbe8b9507,0x3f764d97,0x3df475c0,0x3f7e2b72,0xbecb2aae,0x3f6afb8c,
0x3ef15aea,0x3f61c598,0xbd48fb30,0x3f7fb10f,0x3eb263ef,0x3f6ff573,0xbe3b6ecf,0x3f7baccd,0x3e605c13,0x3f79c79d,0xbea09ae5,0x3f731447,
0x3dafb680,0x3f7f0e58,0xbee0924f,0x3f660f88,0x3ee63375,0x3f64aa59,0xbdafb680,0x3f7f0e58,0x3ea5129f,0x3f725470,0xbe636c83,0x3f799b43,
0x3e419b37,0x3f7b61fc,0xbeb554ec,0x3f6f6830,0x3d55880e,0x3f7fa6e3,0xbef58035,0x3f60a6cf,0x3edae880,0x3f676bd8,0xbdfab273,0x3f7e1324,
0x3e97a117,0x3f748422,0xbe8586ce,0x3f772417,0x3e22abb6,0x3f7cbfc9,0xbec9b953,0x3f6b4b0c,0x3c96c9b6,0x3f7ff4e6,0xbf04f484,0x3f5ac450,
0x3ecf7bca,0x3f6a09a7,0xbe22abb6,0x3f7cbfc9,0x3e8a11f7,0x3f76841b,0xbe9920fe,0x3f74484b,0x3e039502,0x3f7de0b1,0xbeddbe79,0x3f66becc,
0xbc7b514b,0x3f7ff84a,0xbf0ee0db,0x3f546b3b,0x3e47c5c2,0x3f7b14be,0xbef15aea,0x3f61c598,0x3cc90ab0,0x3f7fec43,0xbf1d7fd1,0x3f49d112,
0xbe164083,0x3f7d3aac,0xbf3daef9,0x3f2beb4a,0xbea09ae5,0x3f731447,0xbf584853,0x3f08f59b,0x3e2f10a2,0x3f7c3b28,0xbf00e7e4,0x3f5d2d53,
0xbb490fc6,0x3f7fffb1,0xbf256bcb,0x3f436051,0xbe354098,0x3f7bf531,0xbf44e3f5,0x3f239da9,0xbeb0eacb,0x3f703b37,0xbf5e5aa6,0x3efdbabb,
0x3e164083,0x3f7d3aac,0xbf08f59b,0x3f584853,0xbcfb49ba,0x3f7fe129,0xbf2d1469,0x3f3ca003,0xbe541501,0x3f7a7302,0xbf4bbbf8,0x3f1b02c6,
0xbec1071e,0x3f6d1c1d,0xbf63f473,0x3ee900b7,0x3dfab273,0x3f7e1324,0xbf10d3cd,0x3f531849,0xbd6ea038,0x3f7f90b1,0xbf34768f,0x3f3592e7,
0xbe72b651,0x3f78b47b,0xbf5233c6,0x3f121eb0,0xbed0eb2a,0x3f69b7e4,0xbf6912ae,0x3ed3c867,0x3dc8bd36,0x3f7ec46d,0xbf187fc0,0x3f4d9f02,
0xbdafb680,0x3f7f0e58,0xbf3b8f3b,0x3f2e3bde,0xbe888e93,0x3f76ba07,0xbf584853,0x3f08f59b,0xbee0924f,0x3f660f88,0xbf6db293,0x3ebe1d4a,
0x3d96a905,0x3f7f4e6d,0xbf1ff6cb,0x3f47de65,0xbde7fa9a,0x3f7e5a38,0xbf425b89,0x3f269de3,0xbe97a117,0x3f748422,0xbf5df6be,0x3eff17b2,
0xbeeff7fb,0x3f62241a,0xbf71d19f,0x3ea80b1f,0x3d48fb30,0x3f7fb10f,0xbf273656,0x3f41d870,0xbe1008b7,0x3f7d7474,0xbf48d8b3,0x3f1ebc12,
0xbea68f12,0x3f721352,0xbf633c5a,0x3eebcbbb,0xbeff17b2,0x3f5df6be,0xbf756d97,0x3e919ddd,0x3cc90ab0,0x3f7fec43,0xbf2e3bde,0x3f3b8f3b,
0xbe2bf804,0x3f7c5d3a,0xbf4f0417,0x3f16999f,0xbeb554ec,0x3f6f6830,0xbf6816a8,0x3ed8106b,0xbf06f686,0x3f5988ad,0xbf788486,0x3e75c35a,
0x3f6c835e,0x3ec3ef15,0x3f61c598,0x3ef15aea,0x3f6a09a7,0x3ecf7bca,0x3f5ebe05,0x3efc5d27,0x3f676bd8,0x3edae880,0x3f5b941a,0x3f039c3d,
0x3f64aa59,0x3ee63375,0x3f584853,0x3f08f59b,0x3f676bd8,0x3edae880,0x3f59f26a,0x3f064b82,0x3f644fac,0x3ee79a5d,0x3f5627fe,0x3f0c42c9,
0x3f6106f2,0x3ef41f07,0x3f5233c6,0x3f121eb0,0x3f5d924d,0x3f003a06,0x3f4e1689,0x3f17de12,0x3f61c598,0x3ef15aea,0x3f514d3d,0x3f13682a,
0x3f5df6be,0x3eff17b2,0x3f4cae79,0x3f19c200,0x3f59f26a,0x3f064b82,0x3f47de65,0x3f1ff6cb,0x3f55b993,0x3f0cead0,0x3f42de29,0x3f26050a,
0x3f5b941a,0x3f039c3d,0x3f47de65,0x3f1ff6cb,0x3f570348,0x3f0af1b7,0x3f425b89,0x3f269de3,0x3f5233c6,0x3f121eb0,0x3f3ca003,0x3f2d1469,
0x3f4d26fd,0x3f19210f,0x3f36ad7f,0x3f33587a,0x3f54db31,0x3f0e39da,0x3f3daef9,0x3f2beb4a,0x3f4f7a1f,0x3f15f6d9,0x3f373a23,0x3f32c8c9,
0x3f49d112,0x3f1d7fd1,0x3f3085bb,0x3f396842,0x3f43e200,0x3f24d225,0x3f299415,0x3f3fc767,0x3f4d9f02,0x3f187fc0,0x3f32c8c9,0x3f373a23,
0x3f476085,0x3f209393,0x3f2b561b,0x3f3e35c5,0x3f40d0da,0x3f286605,0x3f239da9,0x3f44e3f5,0x3f39f2ac,0x3f2ff3e6,0x3f1ba299,0x3f4b41fa,
0x3f45e403,0x3f226799,0x3f273656,0x3f41d870,0x3f3ebc1b,0x3f2ac082,0x3f1ebc12,0x3f48d8b3,0x3f373a23,0x3f32c8c9,0x3f15f6d9,0x3f4f7a1f,
0x3f2f61a5,0x3f3a7ca4,0x3f0cead0,0x3f55b993,0x3f3daef9,0x3f2beb4a,0x3f1b02c6,0x3f4bbbf8,0x3f3592e7,0x3f34768f,0x3f11796b,0x3f52a649,
0x3f2d1469,0x3f3ca003,0x3f07a136,0x3f591e6a,0x3f24381a,0x3f446337,0x3efafef7,0x3f5f20db,0x3ec3ef15,0x3f6c835e,0x3dc8bd36,0x3f7ec46d,
0x3ea09ae5,0x3f731447,0x3cc90ab0,0x3f7fec43,0x3e78cfcc,0x3f7853f8,0xbd48fb30,0x3f7fb10f,0x3e2f10a2,0x3f7c3b28,0xbdfab273,0x3f7e1324,
0x3eac7cd4,0x3f710908,0x3d16c32c,0x3f7fd397,0x3e870ada,0x3f76ef5b,0xbd2351cb,0x3f7fcbe2,0x3e419b37,0x3f7b61fc,0xbdee3876,0x3f7e4323,
0x3de7fa9a,0x3f7e5a38,0xbe44b0b9,0x3f7b3bab,0x3e94a031,0x3f74fa0b,0xbcc90ab0,0x3f7fec43,0x3e5a3997,0x3f7a1e84,0xbdd53db9,0x3f7e9bc9,
0x3e09cf86,0x3f7dabcc,0xbe3b6ecf,0x3f7baccd,0x3d621469,0x3f7f9c18,0xbe8586ce,0x3f772417,0x3e78cfcc,0x3f7853f8,0xbdafb680,0x3f7f0e58,
0x3e25c58c,0x3f7c9f8a,0xbe2bf804,0x3f7c5d3a,0x3da3308c,0x3f7f2f9d,0xbe7ee6e1,0x3f77f110,0xbb490fc6,0x3f7fffb1,0xbea80b1f,0x3f71d19f,
0x3e47c5c2,0x3f7b14be,0xbe164083,0x3f7d3aac,0x3de1bc2e,0x3f7e70b0,0xbe6c9a7f,0x3f791298,0x3cc90ab0,0x3f7fec43,0xbea09ae5,0x3f731447,
0xbd7b2b74,0x3f7f84ab,0xbec9b953,0x3f6b4b0c,0x3e164083,0x3f7d3aac,0xbe541501,0x3f7a7302,0x3d6ea038,0x3f7f90b1,0xbe9620d2,0x3f74bf62,
0xbcfb49ba,0x3f7fe129,0xbec1071e,0x3f6d1c1d,0xbdf475c0,0x3f7e2b72,0xbeea6681,0x3f6398ac,0x3dc8bd36,0x3f7ec46d,0xbe888e93,0x3f76ba07,
0x3bc90f88,0x3f7ffec4,0xbeb554ec,0x3f6f6830,0xbdafb680,0x3f7f0e58,0xbee0924f,0x3f660f88,0xbe354098,0x3f7bf531,0xbf04f484,0x3f5ac450,
0x3d48fb30,0x3f7fb10f,0xbea68f12,0x3f721352,0xbd3c6dd5,0x3f7fba9e,0xbed3c867,0x3f6912ae,0xbe1008b7,0x3f7d7474,0xbeff17b2,0x3f5df6be,
0xbe6fa8b2,0x3f78e3d6,0xbf140c5f,0x3f50d937,0xbec3ef15,0x3f6c835e,0xbf45e403,0x3f226799,0xbefc5d27,0x3f5ebe05,0xbf584853,0x3f08f59b,
0xbf187fc0,0x3f4d9f02,0xbf676bd8,0x3edae880,0xbf3085bb,0x3f396842,0xbf731447,0x3ea09ae5,0xbedae880,0x3f676bd8,0xbf4f7a1f,0x3f15f6d9,
0xbf099f4e,0x3f57dc7f,0xbf60a6cf,0x3ef58035,0xbf239da9,0x3f44e3f5,0xbf6e46be,0x3ebb31a0,0xbf3b0629,0x3f2ecef7,0xbf7822d1,0x3e7bdba4,
0xbef15aea,0x3f61c598,0xbf584853,0x3f08f59b,0xbf14b039,0x3f5064af,0xbf6816a8,0x3ed8106b,0xbf2e3bde,0x3f3b8f3b,0xbf740bdd,0x3e9aa086,
0xbf44e3f5,0x3f239da9,0xbf7bf531,0x3e354098,0xbf039c3d,0x3f5b941a,0xbf604621,0x3ef6e0cb,0xbf1f599f,0x3f485bca,0xbf6e8ff8,0x3eb9bb1e,
0xbf385216,0x3f31a81d,0xbf78b47b,0x3e72b651,0xbf4e1689,0x3f17de12,0xbf7e868b,0x3ddb7d37,0xbf0e39da,0x3f54db31,0xbf676bd8,0x3edae880,
0xbf299415,0x3f3fc767,0xbf740bdd,0x3e9aa086,0xbf41d870,0x3f273656,0xbf7c3b28,0x3e2f10a2,0xbf5695e5,0x3f0b9a6b,0xbf7fd397,0x3d16c32c,
0xbf187fc0,0x3f4d9f02,0xbf6db293,0x3ebe1d4a,0xbf33587a,0x3f36ad7f,0xbf788486,0x3e75c35a,0xbf4ac77f,0x3f1c420c,0xbf7e9bc9,0x3dd53db9,
0xbf5e5aa6,0x3efdbabb,0xbf7fdaaf,0xbd0a342f,0xbf226799,0x3f45e403,0xbf731447,0x3ea09ae5,0xbf3ca003,0x3f2d1469,0xbf7bf531,0x3e354098,
0xbf531849,0x3f10d3cd,0xbf7fd397,0x3d16c32c,0xbf655e0b,0x3ee363fa,0xbf7e9bc9,0xbdd53db9,0xbf2beb4a,0x3f3daef9,0xbf778bc5,0x3e827dc0,
0xbf456439,0x3f2302d3,0xbf7e5a38,0x3de7fa9a,0xbf5ac450,0x3f04f484,0xbf7fe129,0xbcfb49ba,0xbf6b99fb,0x3ec8477c,0xbf7c187a,0xbe3228d4,
0xbf6c835e,0x3ec3ef15,0xbf74fa0b,0xbe94a031,0xbf79c79d,0x3e605c13,0xbf64aa59,0xbee63375,0xbf7fb10f,0x3d48fb30,0xbf4d9f02,0xbf187fc0,
0xbf7e1324,0xbdfab273,0xbf3085bb,0xbf396842,0xbf710908,0x3eac7cd4,0xbf6ff573,0xbeb263ef,0xbf7c5d3a,0x3e2bf804,0xbf5cc7d1,0xbf019573,
0xbf7ffec4,0xbbc90f88,0xbf42de29,0xbf26050a,0xbf7bd14d,0xbe3857ec,0xbf2302d3,0xbf456439,0xbf74fa0b,0x3e94a031,0xbf6a09a7,0xbecf7bca,
0xbf7e4323,0x3dee3876,0xbf53fac3,0xbf0f8784,0xbf7f84ab,0xbd7b2b74,0xbf373a23,0xbf32c8c9,0xbf78b47b,0xbe72b651,0xbf14b039,0xbf5064af,
0xbf7853f8,0x3e78cfcc,0xbf633c5a,0xbeebcbbb,0xbf7f7808,0x3d83db0a,0xbf4a4c87,0xbf1ce11f,0xbf7e4323,0xbdee3876,0xbf2ac082,0xbf3ebc1b,
0xbf74bf62,0xbe9620d2,0xbf05a02c,0xbf5a5ba0,0xbf7b14be,0x3e47c5c2,0xbf5b941a,0xbf039c3d,0xbf7ffb11,0x3c490e90,0xbf3fc767,0xbf299415,
0xbf7c3b28,0xbe2f10a2,0xbf1d7fd1,0xbf49d112,0xbf6ff573,0xbeb263ef,0xbeebcbbb,0xbf633c5a,0xbf7d3aac,0x3e164083,0xbf531849,0xbf10d3cd,
0xbf7fcbe2,0xbd2351cb,0xbf34768f,0xbf3592e7,0xbf796e4e,0xbe667c66,0xbf0f8784,0xbf53fac3,0xbf6a5ad9,0xbece0bea,0xbecb2aae,0xbf6afb8c,
0xbf7ec46d,0x3dc8bd36,0xbf49d112,0xbf1d7fd1,0xbf7eea9d,0xbdbc3ac3,0xbf286605,0xbf40d0da,0xbf75dec6,0xbe8e9a22,0xbf00e7e4,0xbf5d2d53,
0xbf63f473,0xbee900b7,0xbea986c4,0xbf718f57,0xbf7fb10f,0x3d48fb30,0xbf3fc767,0xbf299415,0xbf7d57de,0xbe1324ca,0xbf1ba299,0xbf4b41fa,
0xbf718f57,0xbea986c4,0xbee363fa,0xbf655e0b,0xbf5cc7d1,0xbf019573,0xbe870ada,0xbf76ef5b,0x3f54db31,0x3f0e39da,0x3f45e403,0x3f226799,
0x3f514d3d,0x3f13682a,0x3f41d870,0x3f273656,0x3f4d9f02,0x3f187fc0,0x3f3daef9,0x3f2beb4a,0x3f49d112,0x3f1d7fd1,0x3f396842,0x3f3085bb,
0x3f49d112,0x3f1d7fd1,0x3f373a23,0x3f32c8c9,0x3f456439,0x3f2302d3,0x3f3238aa,0x3f37c655,0x3f40d0da,0x3f286605,0x3f2d1469,0x3f3ca003,
0x3f3c17d9,0x3f2da859,0x3f27ce61,0x3f4154e1,0x3f3daef9,0x3f2beb4a,0x3f273656,0x3f41d870,0x3f385216,0x3f31a81d,0x3f212ff9,0x3f46e22a,
0x3f32c8c9,0x3f373a23,0x3f1b02c6,0x3f4bbbf8,0x3f2d1469,0x3f3ca003,0x3f14b039,0x3f5064af,0x3f3085bb,0x3f396842,0x3f15f6d9,0x3f4f7a1f,
0x3f2a2a80,0x3f3f41fc,0x3f0ee0db,0x3f546b3b,0x3f239da9,0x3f44e3f5,0x3f07a136,0x3f591e6a,0x3f1ce11f,0x3f4a4c87,0x3f003a06,0x3f5d924d,
0x3f226799,0x3f45e403,0x3f039c3d,0x3f5b941a,0x3f1b02c6,0x3f4bbbf8,0x3ef6e0cb,0x3f604621,0x3f13682a,0x3f514d3d,0x3ee63375,0x3f64aa59,
0x3f0b9a6b,0x3f5695e5,0x3ed53641,0x3f68bf3c,0x3f13682a,0x3f514d3d,0x3ee0924f,0x3f660f88,0x3f0af1b7,0x3f570348,0x3ece0bea,0x3f6a5ad9,
0x3f0242b1,0x3f5c61c7,0x3ebb31a0,0x3f6e46be,0x3ef2bd43,0x3f61668a,0x3ea80b1f,0x3f71d19f,0x3f039c3d,0x3f5b941a,0x3eb8442a,0x3f6ed89e,
0x3ef41f07,0x3f6106f2,0x3ea395c5,0x3f7294f8,0x3ee0924f,0x3f660f88,0x3e8e9a22,0x3f75dec6,0x3ecc9b8b,0x3f6aab7b,0x3e72b651,0x3f78b47b,
0x3ee63375,0x3f64aa59,0x3e8e9a22,0x3f75dec6,0x3ed0eb2a,0x3f69b7e4,0x3e6fa8b2,0x3f78e3d6,0x3ebb31a0,0x3f6e46be,0x3e419b37,0x3f7b61fc,
0x3ea5129f,0x3f725470,0x3e1324ca,0x3f7d57de,0xbe47c5c2,0x3f7b14be,0xbef15aea,0x3f61c598,0xbe888e93,0x3f76ba07,0xbf08f59b,0x3f584853,
0xbeac7cd4,0x3f710908,0xbf187fc0,0x3f4d9f02,0xbecf7bca,0x3f6a09a7,0xbf273656,0x3f41d870,0xbe888e93,0x3f76ba07,0xbf0b9a6b,0x3f5695e5,
0xbeadf73c,0x3f70c501,0xbf1ba299,0x3f4b41fa,0xbed25a09,0x3f696591,0xbf2ac082,0x3f3ebc1b,0xbef58035,0x3f60a6cf,0xbf38dd65,0x3f311722,
0xbeac7cd4,0x3f710908,0xbf1d7fd1,0x3f49d112,0xbed25a09,0x3f696591,0xbf2d1469,0x3f3ca003,0xbef6e0cb,0x3f604621,0xbf3b8f3b,0x3f2e3bde,
0xbf0cead0,0x3f55b993,0xbf48d8b3,0x3f1ebc12,0xbecf7bca,0x3f6a09a7,0xbf2e3bde,0x3f3b8f3b,0xbef58035,0x3f60a6cf,0xbf3d27b8,0x3f2c800f,
0xbf0cead0,0x3f55b993,0xbf4ac77f,0x3f1c420c,0xbf1e1e22,0x3f495521,0xbf570348,0x3f0af1b7,0xbef15aea,0x3f61c598,0xbf3daef9,0x3f2beb4a,
0xbf0b9a6b,0x3f5695e5,0xbf4bbbf8,0x3f1b02c6,0xbf1d7fd1,0x3f49d112,0xbf584853,0x3f08f59b,0xbf2e3bde,0x3f3b8f3b,0xbf633c5a,0x3eebcbbb,
0xbf08f59b,0x3f584853,0xbf4bbbf8,0x3f1b02c6,0xbf1ba299,0x3f4b41fa,0xbf58b3a1,0x3f084b92,0xbf2d1469,0x3f3ca003,0xbf63f473,0x3ee900b7,
0xbf3d27b8,0x3f2c800f,0xbf6d67a1,0x3ebf926f,0xbf187fc0,0x3f4d9f02,0xbf584853,0x3f08f59b,0xbf2ac082,0x3f3ebc1b,0xbf63f473,0x3ee900b7,
0xbf3b8f3b,0x3f2e3bde,0xbf6db293,0x3ebe1d4a,0xbf4ac77f,0x3f1c420c,0xbf756d97,0x3e919ddd,0xbf273656,0x3f41d870,0xbf633c5a,0x3eebcbbb,
0xbf38dd65,0x3f311722,0xbf6d67a1,0x3ebf926f,0xbf48d8b3,0x3f1ebc12,0xbf756d97,0x3e919ddd,0xbf570348,0x3f0af1b7,0xbf7b3bab,0x3e44b0b9,
0xbf7b14be,0x3e47c5c2,0xbf74fa0b,0xbe94a031,0xbf7f4e6d,0x3d96a905,0xbf6a09a7,0xbecf7bca,0xbf7fb10f,0xbd48fb30,0xbf5b941a,0xbf039c3d,
0xbf7c3b28,0xbe2f10a2,0xbf49d112,0xbf1d7fd1,0xbf7e1324,0x3dfab273,0xbf6db293,0xbebe1d4a,0xbf7fffb1,0xbb490fc6,0xbf5fe4e9,0xbef840c8,
0xbf7de0b1,0xbe039502,0xbf4e8d90,0xbf173c07,0xbf77beb7,0xbe80f8c0,0xbf39f2ac,0xbf2ff3e6,0xbf7fb10f,0x3d48fb30,0xbf64aa59,0xbee63375,
0xbf7f2f9d,0xbda3308c,0xbf53fac3,0xbf0f8784,0xbf7a7302,0xbe541501,0xbf3fc767,0xbf299415,0xbf718f57,0xbea986c4,0xbf286605,0xbf40d0da,
0xbf7fec43,0xbcc90ab0,0xbf59f26a,0xbf064b82,0xbf7cdf6c,0xbe1f917b,0xbf466354,0xbf21cbfb,0xbf756d97,0xbe919ddd,0xbf2f61a5,0xbf3a7ca4,
0xbf69b7e4,0xbed0eb2a,0xbf1553b7,0xbf4fefa8,0xbf7ec46d,0xbdc8bd36,0xbf4d9f02,0xbf187fc0,0xbf791298,0xbe6c9a7f,0xbf373a23,0xbf32c8c9,
0xbf6ed89e,0xbeb8442a,0xbf1d7fd1,0xbf49d112,0xbf604621,0xbef6e0cb,0xbf00e7e4,0xbf5d2d53,0xbf7c3b28,0xbe2f10a2,0xbf3fc767,0xbf299415,
0xbf73ced9,0xbe9c1faf,0xbf269de3,0xbf425b89,0xbf66becc,0xbeddbe79,0xbf0a48ad,0xbf577026,0xbf554aa4,0xbf0d9281,0xbed6a399,0xbf686b39,
0xbf7853f8,0xbe78cfcc,0xbf3085bb,0xbf396842,0xbf6d1c1d,0xbec1071e,0xbf14b039,0xbf5064af,0xbf5d2d53,0xbf00e7e4,0xbeebcbbb,0xbf633c5a,
0xbf48d8b3,0xbf1ebc12,0xbea986c4,0xbf718f57,0xbf731447,0xbea09ae5,0xbf1ff6cb,0xbf47de65,0xbf650479,0xbee4cbfe,0xbf019573,0xbf5cc7d1,
0xbf5233c6,0xbf121eb0,0xbec1071e,0xbf6d1c1d,0xbf3b0629,0xbf2ecef7,0xbe75c35a,0xbf788486,0xbf0e39da,0xbf54db31,0x3dc8bd36,0xbf7ec46d,
0xbecf7bca,0xbf6a09a7,0x3e888e93,0xbf76ba07,0xbe78cfcc,0xbf7853f8,0x3edae880,0xbf676bd8,0xbd96a905,0xbf7f4e6d,0x3f13682a,0xbf514d3d,
0xbefc5d27,0xbf5ebe05,0x3e3b6ecf,0xbf7baccd,0xbeab0201,0xbf714c7a,0x3eb3dca5,0xbf6faf1b,0xbe28defc,0xbf7c7eb0,0x3f0242b1,0xbf5c61c7,
0x3c16cb58,0xbf7ffd39,0x3f269de3,0xbf425b89,0xbedae880,0xbf676bd8,0x3e888e93,0xbf76ba07,0xbe8586ce,0xbf772417,0x3eddbe79,0xbf66becc,
0xbdafb680,0xbf7f0e58,0x3f15f6d9,0xbf4f7a1f,0x3dbc3ac3,0xbf7eea9d,0x3f385216,0xbf31a81d,0xbeb8442a,0xbf6ed89e,0x3eb263ef,0xbf6ff573,
0xbe3e853e,0xbf7b87b2,0x3f02ef9f,0xbf5bfb34,0xbbc90f88,0xbf7ffec4,0x3f286605,0xbf40d0da,0x3e3228d4,0xbf7c187a,0x3f485bca,0xbf1f599f,
0xbe94a031,0xbf74fa0b,0x3edae880,0xbf676bd8,0xbde1bc2e,0xbf7e70b0,0x3f15f6d9,0xbf4f7a1f,0x3d96a905,0xbf7f4e6d,0x3f396842,0xbf3085bb,
0x3e827dc0,0xbf778bc5,0x3f5695e5,0xbf0b9a6b,0xbe605c13,0xbf79c79d,0x3f00e7e4,0xbf5d2d53,0xbd0a342f,0xbf7fdaaf,0x3f27ce61,0xbf4154e1,
0x3e1c76de,0xbf7cfe73,0x3f48d8b3,0xbf1ebc12,0x3eab0201,0xbf714c7a,0x3f62df7b,0xbeed3063,0xbe164083,0xbf7d3aac,0x3f13682a,0xbf514d3d,
0x3d2fe007,0xbf7fc38f,0x3f385216,0xbf31a81d,0x3e6c9a7f,0xbf791298,0x3f5695e5,0xbf0b9a6b,0x3ed25a09,0xbf696591,0x3f6d1c1d,0xbec1071e,
0xbd96a905,0xbf7f4e6d,0x3f24d225,0xbf43e200,0x3df475c0,0xbf7e2b72,0x3f476085,0xbf209393,0x3e9d9e78,0xbf73913f,0x3f628210,0xbeee9479,
0x3ef840c8,0xbf5fe4e9,0x3f75341d,0xbe931f35,
};

__device__ __align__(1024) __nv_bfloat16 g_Z[340 * 4096];
__device__ __align__(1024) uint32_t      g_Wt[321 * 2048];
__device__ __align__(1024) __nv_bfloat16 g_Y[352 * 4096];
__device__ __align__(1024) __nv_bfloat16 g_h[2048 * 640];
__device__ __align__(1024) __nv_bfloat16 g_ln2[2048 * 640];
__device__ __align__(1024) __nv_bfloat16 g_hh[2048 * 1536];
__device__ __align__(1024) __nv_bfloat16 g_w2t[640 * 1536];
#define SY_B1   0
#define SY_W    16
#define SY_B2   32
#define SY_W2T  48
#define SY_F3   64
#define SY_F4   80
#define SY_N    128
__device__ __align__(1024) unsigned int  g_sync[SY_N * 32];

#define PROF(i)
#define PROFC(i)
#define TRC(it, j)
__device__ __forceinline__ uint32_t smem_u32(const void* p) { return (uint32_t)__cvta_generic_to_shared(p); }
__device__ __forceinline__ void mbar_init(uint32_t bar, int cnt) { asm volatile("mbarrier.init.shared::cta.b64 [%0], %1;" ::"r"(bar), "r"(cnt)); }
__device__ __forceinline__ void mbar_expect_tx(uint32_t bar, int bytes) {
  asm volatile("mbarrier.arrive.expect_tx.shared::cta.b64 _, [%0], %1;" ::"r"(bar), "r"(bytes) : "memory");
}
__device__ __forceinline__ void mbar_arrive(uint32_t bar) { asm volatile("mbarrier.arrive.shared::cta.b64 _, [%0];" ::"r"(bar) : "memory"); }
__device__ __forceinline__ void mbar_wait(uint32_t bar, int parity) {
  uint32_t ok;
  uint32_t guard = 0;
  do {
    asm volatile("{\n.reg .pred p;\nmbarrier.try_wait.parity.shared::cta.b64 p, [%1], %2;\nselp.u32 %0, 1, 0, p;\n}\n"
                 : "=r"(ok) : "r"(bar), "r"(parity) : "memory");
    if (++guard > (1u << 22)) break;
  } while (!ok);
}
__device__ __forceinline__ uint32_t mbar_test(uint32_t bar, int parity) {
  uint32_t ok;
  asm volatile("{\n.reg .pred p;\nmbarrier.test_wait.parity.shared::cta.b64 p, [%1], %2;\nselp.u32 %0, 1, 0, p;\n}\n"
               : "=r"(ok) : "r"(bar), "r"(parity) : "memory");
  return ok;
}
__device__ __forceinline__ void mbar_arrive_if(uint32_t bar, uint32_t pred) {
  asm volatile("{\n.reg .pred p;\nsetp.ne.u32 p, %1, 0;\n@p mbarrier.arrive.shared::cta.b64 _, [%0];\n}\n" ::"r"(bar), "r"(pred) : "memory");
}
__device__ __forceinline__ void tma_load_2d(uint32_t dst, const CUtensorMap* map, uint32_t bar, int c0, int c1) {
  asm volatile("cp.async.bulk.tensor.2d.shared::cluster.global.mbarrier::complete_tx::bytes [%0], [%1, {%3, %4}], [%2];"
               ::"r"(dst), "l"(map), "r"(bar), "r"(c0), "r"(c1) : "memory");
}
__device__ __forceinline__ void tma_load_3d(uint32_t dst, const CUtensorMap* map, uint32_t bar, int c0, int c1, int c2) {
  asm volatile("cp.async.bulk.tensor.3d.shared::cluster.global.mbarrier::complete_tx::bytes [%0], [%1, {%3, %4, %5}], [%2];"
               ::"r"(dst), "l"(map), "r"(bar), "r"(c0), "r"(c1), "r"(c2) : "memory");
}
__device__ __forceinline__ void tma_load_5d(uint32_t dst, const CUtensorMap* map, uint32_t bar, int c0, int c4) {
  asm volatile("cp.async.bulk.tensor.5d.shared::cluster.global.mbarrier::complete_tx::bytes [%0], [%1, {%3, %4, %4, %4, %5}], [%2];"
               ::"r"(dst), "l"(map), "r"(bar), "r"(c0), "r"(0), "r"(c4) : "memory");
}
__device__ __forceinline__ void tma_store_2d(const CUtensorMap* map, uint32_t src, int c0, int c1) {
  asm volatile("cp.async.bulk.tensor.2d.global.shared::cta.bulk_group [%0, {%2, %3}], [%1];"
               ::"l"(map), "r"(src), "r"(c0), "r"(c1) : "memory");
}
__device__ __forceinline__ void bulk_load(uint32_t dst, const void* src, uint32_t bytes, uint32_t bar) {
  asm volatile("cp.async.bulk.shared::cluster.global.mbarrier::complete_tx::bytes [%0], [%1], %2, [%3];"
               ::"r"(dst), "l"(src), "r"(bytes), "r"(bar) : "memory");
}
__device__ __forceinline__ void bulk_prefetch_l2(const void* src, uint32_t bytes) {
  asm volatile("cp.async.bulk.prefetch.L2.global [%0], %1;" ::"l"(src), "r"(bytes) : "memory");
}
__device__ __forceinline__ void bulk_commit() { asm volatile("cp.async.bulk.commit_group;" ::: "memory"); }
__device__ __forceinline__ void bulk_wait0() { asm volatile("cp.async.bulk.wait_group 0;" ::: "memory"); }
__device__ __forceinline__ void fence_async_smem() { asm volatile("fence.proxy.async.shared::cta;" ::: "memory"); }
__device__ __forceinline__ void fence_async_global() { asm volatile("fence.proxy.async.global;" ::: "memory"); }
__device__ __forceinline__ void prefetch_tmap(const CUtensorMap* m) { asm volatile("prefetch.tensormap [%0];" ::"l"(m) : "memory"); }
__device__ __forceinline__ void named_bar(int id, int n) { asm volatile("bar.sync %0, %1;" ::"r"(id), "r"(n) : "memory"); }
__device__ __forceinline__ void wg_fence() { asm volatile("wgmma.fence.sync.aligned;" ::: "memory"); }
__device__ __forceinline__ void wg_commit() { asm volatile("wgmma.commit_group.sync.aligned;" ::: "memory"); }
template <int N> __device__ __forceinline__ void wg_wait() { asm volatile("wgmma.wait_group.sync.aligned %0;" ::"n"(N) : "memory"); }
__device__ __forceinline__ uint64_t mkdesc(uint32_t addr, uint32_t lbo, uint32_t sbo, uint32_t swz) {
  return (uint64_t)((addr & 0x3FFFF) >> 4) | ((uint64_t)(lbo >> 4) << 16) | ((uint64_t)(sbo >> 4) << 32) | ((uint64_t)swz << 62);
}
__device__ __forceinline__ uint32_t pack_bf16(float lo, float hi) {
  uint32_t r;
  asm("cvt.rn.bf16x2.f32 %0, %1, %2;" : "=r"(r) : "f"(hi), "f"(lo));
  return r;
}
__device__ __forceinline__ float bf_lo(uint32_t w) { return __uint_as_float(w << 16); }
__device__ __forceinline__ float bf_hi(uint32_t w) { return __uint_as_float(w & 0xFFFF0000u); }
__device__ __forceinline__ float bfr(float x) { return __bfloat162float(__float2bfloat16_rn(x)); }
__device__ __forceinline__ void mma16(float (&d)[4], uint32_t a0, uint32_t a1, uint32_t a2, uint32_t a3, uint32_t b0, uint32_t b1) {
  asm volatile("mma.sync.aligned.m16n8k16.row.col.f32.bf16.bf16.f32 {%0,%1,%2,%3}, {%4,%5,%6,%7}, {%8,%9}, {%0,%1,%2,%3};"
               : "+f"(d[0]), "+f"(d[1]), "+f"(d[2]), "+f"(d[3]) : "r"(a0), "r"(a1), "r"(a2), "r"(a3), "r"(b0), "r"(b1));
}
__device__ __forceinline__ void mma8(float (&d)[4], uint32_t a0, uint32_t a1, uint32_t b0) {
  asm volatile("mma.sync.aligned.m16n8k8.row.col.f32.bf16.bf16.f32 {%0,%1,%2,%3}, {%4,%5}, {%6}, {%0,%1,%2,%3};"
               : "+f"(d[0]), "+f"(d[1]), "+f"(d[2]), "+f"(d[3]) : "r"(a0), "r"(a1), "r"(b0));
}
__device__ __forceinline__ void ldsm4t(uint32_t (&r)[4], uint32_t addr) {
  asm volatile("ldmatrix.sync.aligned.m8n8.x4.trans.shared.b16 {%0,%1,%2,%3}, [%4];"
               : "=r"(r[0]), "=r"(r[1]), "=r"(r[2]), "=r"(r[3]) : "r"(addr) : "memory");
}
__device__ __forceinline__ void stsm4(uint32_t addr, uint32_t r0, uint32_t r1, uint32_t r2, uint32_t r3) {
  asm volatile("stmatrix.sync.aligned.m8n8.x4.shared.b16 [%0], {%1,%2,%3,%4};" ::"r"(addr), "r"(r0), "r"(r1), "r"(r2), "r"(r3) : "memory");
}
__device__ __forceinline__ void sts64(uint32_t addr, uint32_t a, uint32_t b) { asm volatile("st.shared.v2.b32 [%0], {%1,%2};" ::"r"(addr), "r"(a), "r"(b) : "memory"); }
__device__ __forceinline__ void sts32(uint32_t addr, uint32_t a) { asm volatile("st.shared.b32 [%0], %1;" ::"r"(addr), "r"(a) : "memory"); }
__device__ __forceinline__ void sts128(uint32_t addr, uint32_t a, uint32_t b, uint32_t c, uint32_t d) {
  asm volatile("st.shared.v4.b32 [%0], {%1,%2,%3,%4};" ::"r"(addr), "r"(a), "r"(b), "r"(c), "r"(d) : "memory");
}
__device__ __forceinline__ void sts64p(uint32_t addr, uint32_t a, uint32_t b, uint32_t p) {
  asm volatile("{\n.reg .pred q;\nsetp.ne.u32 q, %3, 0;\n@q st.shared.v2.b32 [%0], {%1,%2};\n}\n" ::"r"(addr), "r"(a), "r"(b), "r"(p) : "memory");
}
__device__ __forceinline__ void sts32p(uint32_t addr, uint32_t a, uint32_t p) {
  asm volatile("{\n.reg .pred q;\nsetp.ne.u32 q, %2, 0;\n@q st.shared.b32 [%0], %1;\n}\n" ::"r"(addr), "r"(a), "r"(p) : "memory");
}
__device__ __forceinline__ void stsm4p(uint32_t addr, uint32_t r0, uint32_t r1, uint32_t r2, uint32_t r3, uint32_t p) {
  asm volatile("{\n.reg .pred q;\nsetp.ne.u32 q, %5, 0;\n@q stmatrix.sync.aligned.m8n8.x4.shared.b16 [%0], {%1,%2,%3,%4};\n}\n"
               ::"r"(addr), "r"(r0), "r"(r1), "r"(r2), "r"(r3), "r"(p) : "memory");
}
__device__ __forceinline__ void stg128p(void* ptr, uint32_t a, uint32_t b, uint32_t c, uint32_t d, uint32_t p) {
  asm volatile("{\n.reg .pred q;\nsetp.ne.u32 q, %5, 0;\n@q st.global.v4.b32 [%0], {%1,%2,%3,%4};\n}\n" ::"l"(ptr), "r"(a), "r"(b), "r"(c), "r"(d), "r"(p) : "memory");
}
__device__ __forceinline__ void stg128(void* p, uint32_t a, uint32_t b, uint32_t c, uint32_t d) {
  asm volatile("st.global.v4.b32 [%0], {%1,%2,%3,%4};" ::"l"(p), "r"(a), "r"(b), "r"(c), "r"(d) : "memory");
}
__device__ __forceinline__ uint2 lds64(uint32_t addr) { uint2 v; asm volatile("ld.shared.v2.b32 {%0,%1}, [%2];" : "=r"(v.x), "=r"(v.y) : "r"(addr) : "memory"); return v; }
__device__ __forceinline__ uint4 lds128(uint32_t addr) {
  uint4 v; asm volatile("ld.shared.v4.b32 {%0,%1,%2,%3}, [%4];" : "=r"(v.x), "=r"(v.y), "=r"(v.z), "=r"(v.w) : "r"(addr) : "memory"); return v;
}
__device__ __forceinline__ unsigned int ld_acquire(const unsigned int* p) {
  unsigned int v; asm volatile("ld.acquire.gpu.global.u32 %0, [%1];" : "=r"(v) : "l"(p) : "memory"); return v;
}
__device__ __forceinline__ void red_release(unsigned int* p) { asm volatile("red.release.gpu.global.add.u32 [%0], 1;" ::"l"(p) : "memory"); }
__device__ __forceinline__ void red_relaxed(unsigned int* p) { asm volatile("red.relaxed.gpu.global.add.u32 [%0], 1;" ::"l"(p) : "memory"); }
__device__ __forceinline__ void bulk_store(void* dst, uint32_t src, uint32_t bytes) {
  asm volatile("cp.async.bulk.global.shared::cta.bulk_group [%0], [%1], %2;" ::"l"(dst), "r"(src), "r"(bytes) : "memory");
}
__device__ __forceinline__ void ldsm4t_v(uint32_t (&r)[4], uint32_t addr) { ldsm4t(r, addr); }
__device__ __forceinline__ void wait_flag(const unsigned int* p, unsigned int target) {
  uint32_t guard = 0;
  while (ld_acquire(p) < target) { if (++guard > (1u << 21)) break; }
}

template <int TB, int SA = 1, int SB = 1>
__device__ __forceinline__ void wgmma_rs_n64(float (&d)[32], uint32_t a0, uint32_t a1, uint32_t a2, uint32_t a3, uint64_t db, int scale_d) {
  asm volatile("{\n.reg .pred p;\nsetp.ne.b32 p, %37, 0;\n"
    "wgmma.mma_async.sync.aligned.m64n64k16.f32.bf16.bf16 {%0, %1, %2, %3, %4, %5, %6, %7, %8, %9, %10, %11, %12, %13, %14, %15, %16, %17, %18, %19, %20, %21, %22, %23, %24, %25, %26, %27, %28, %29, %30, %31}, {%32, %33, %34, %35}, %36, p, %39, %40, %38;\n}\n"
    : "+f"(d[0]), "+f"(d[1]), "+f"(d[2]), "+f"(d[3]), "+f"(d[4]), "+f"(d[5]), "+f"(d[6]), "+f"(d[7]), "+f"(d[8]), "+f"(d[9]), "+f"(d[10]), "+f"(d[11]), "+f"(d[12]), "+f"(d[13]), "+f"(d[14]), "+f"(d[15]), "+f"(d[16]), "+f"(d[17]), "+f"(d[18]), "+f"(d[19]), "+f"(d[20]), "+f"(d[21]), "+f"(d[22]), "+f"(d[23]), "+f"(d[24]), "+f"(d[25]), "+f"(d[26]), "+f"(d[27]), "+f"(d[28]), "+f"(d[29]), "+f"(d[30]), "+f"(d[31])
    : "r"(a0), "r"(a1), "r"(a2), "r"(a3), "l"(db), "r"(scale_d), "n"(TB), "n"(SA), "n"(SB));
}
template <int TA, int TB, int SA = 1, int SB = 1>
__device__ __forceinline__ void wgmma_ss_n64(float (&d)[32], uint64_t da, uint64_t db, int scale_d) {
  asm volatile("{\n.reg .pred p;\nsetp.ne.b32 p, %34, 0;\n"
    "wgmma.mma_async.sync.aligned.m64n64k16.f32.bf16.bf16 {%0, %1, %2, %3, %4, %5, %6, %7, %8, %9, %10, %11, %12, %13, %14, %15, %16, %17, %18, %19, %20, %21, %22, %23, %24, %25, %26, %27, %28, %29, %30, %31}, %32, %33, p, %37, %38, %35, %36;\n}\n"
    : "+f"(d[0]), "+f"(d[1]), "+f"(d[2]), "+f"(d[3]), "+f"(d[4]), "+f"(d[5]), "+f"(d[6]), "+f"(d[7]), "+f"(d[8]), "+f"(d[9]), "+f"(d[10]), "+f"(d[11]), "+f"(d[12]), "+f"(d[13]), "+f"(d[14]), "+f"(d[15]), "+f"(d[16]), "+f"(d[17]), "+f"(d[18]), "+f"(d[19]), "+f"(d[20]), "+f"(d[21]), "+f"(d[22]), "+f"(d[23]), "+f"(d[24]), "+f"(d[25]), "+f"(d[26]), "+f"(d[27]), "+f"(d[28]), "+f"(d[29]), "+f"(d[30]), "+f"(d[31])
    : "l"(da), "l"(db), "r"(scale_d), "n"(TA), "n"(TB), "n"(SA), "n"(SB));
}
template <int TA, int TB, int SA = 1, int SB = 1>
__device__ __forceinline__ void wgmma_ss_n80(float (&d)[40], uint64_t da, uint64_t db, int scale_d) {
  asm volatile("{\n.reg .pred p;\nsetp.ne.b32 p, %42, 0;\n"
    "wgmma.mma_async.sync.aligned.m64n80k16.f32.bf16.bf16 {%0, %1, %2, %3, %4, %5, %6, %7, %8, %9, %10, %11, %12, %13, %14, %15, %16, %17, %18, %19, %20, %21, %22, %23, %24, %25, %26, %27, %28, %29, %30, %31, %32, %33, %34, %35, %36, %37, %38, %39}, %40, %41, p, %45, %46, %43, %44;\n}\n"
    : "+f"(d[0]), "+f"(d[1]), "+f"(d[2]), "+f"(d[3]), "+f"(d[4]), "+f"(d[5]), "+f"(d[6]), "+f"(d[7]), "+f"(d[8]), "+f"(d[9]), "+f"(d[10]), "+f"(d[11]), "+f"(d[12]), "+f"(d[13]), "+f"(d[14]), "+f"(d[15]), "+f"(d[16]), "+f"(d[17]), "+f"(d[18]), "+f"(d[19]), "+f"(d[20]), "+f"(d[21]), "+f"(d[22]), "+f"(d[23]), "+f"(d[24]), "+f"(d[25]), "+f"(d[26]), "+f"(d[27]), "+f"(d[28]), "+f"(d[29]), "+f"(d[30]), "+f"(d[31]), "+f"(d[32]), "+f"(d[33]), "+f"(d[34]), "+f"(d[35]), "+f"(d[36]), "+f"(d[37]), "+f"(d[38]), "+f"(d[39])
    : "l"(da), "l"(db), "r"(scale_d), "n"(TA), "n"(TB), "n"(SA), "n"(SB));
}
template <int TA, int TB, int SA = 1, int SB = 1>
__device__ __forceinline__ void wgmma_ss_n128(float (&d)[64], uint64_t da, uint64_t db, int scale_d) {
  asm volatile("{\n.reg .pred p;\nsetp.ne.b32 p, %66, 0;\n"
    "wgmma.mma_async.sync.aligned.m64n128k16.f32.bf16.bf16 {%0, %1, %2, %3, %4, %5, %6, %7, %8, %9, %10, %11, %12, %13, %14, %15, %16, %17, %18, %19, %20, %21, %22, %23, %24, %25, %26, %27, %28, %29, %30, %31, %32, %33, %34, %35, %36, %37, %38, %39, %40, %41, %42, %43, %44, %45, %46, %47, %48, %49, %50, %51, %52, %53, %54, %55, %56, %57, %58, %59, %60, %61, %62, %63}, %64, %65, p, %69, %70, %67, %68;\n}\n"
    : "+f"(d[0]), "+f"(d[1]), "+f"(d[2]), "+f"(d[3]), "+f"(d[4]), "+f"(d[5]), "+f"(d[6]), "+f"(d[7]), "+f"(d[8]), "+f"(d[9]), "+f"(d[10]), "+f"(d[11]), "+f"(d[12]), "+f"(d[13]), "+f"(d[14]), "+f"(d[15]), "+f"(d[16]), "+f"(d[17]), "+f"(d[18]), "+f"(d[19]), "+f"(d[20]), "+f"(d[21]), "+f"(d[22]), "+f"(d[23]), "+f"(d[24]), "+f"(d[25]), "+f"(d[26]), "+f"(d[27]), "+f"(d[28]), "+f"(d[29]), "+f"(d[30]), "+f"(d[31]), "+f"(d[32]), "+f"(d[33]), "+f"(d[34]), "+f"(d[35]), "+f"(d[36]), "+f"(d[37]), "+f"(d[38]), "+f"(d[39]), "+f"(d[40]), "+f"(d[41]), "+f"(d[42]), "+f"(d[43]), "+f"(d[44]), "+f"(d[45]), "+f"(d[46]), "+f"(d[47]), "+f"(d[48]), "+f"(d[49]), "+f"(d[50]), "+f"(d[51]), "+f"(d[52]), "+f"(d[53]), "+f"(d[54]), "+f"(d[55]), "+f"(d[56]), "+f"(d[57]), "+f"(d[58]), "+f"(d[59]), "+f"(d[60]), "+f"(d[61]), "+f"(d[62]), "+f"(d[63])
    : "l"(da), "l"(db), "r"(scale_d), "n"(TA), "n"(TB), "n"(SA), "n"(SB));
}

#define SM_A      0
#define SM_B      163840
#define SM_TOTAL  229376
#define SM_TB     0
#define SM_XS     0
#define SM_ZS     24576
#define SM_YS     0
#define SM_YST    24576
#define SM_WS     50176
#define SM_LS     50176
#define SM_T1     71680
#define SM_T3     81920
#define SM_FR     91136
#define SM_FI     99328
#define SM_M2     107520
#define SM_TW     115712
#define SM_WST    132096
#define SM_XR     132096
#define SM_OS     0

struct Bars {
  uint64_t cst1, cst2, xarr, hs, wrdy, p2d, b1p, wraw, T[3], Y, Y2, fullA[10], emptyA[10], fullB[4], emptyB[4], fullG[8], emptyG[8], bfree, f4l[3];
};

__device__ __forceinline__ void ln_stats_partial(const uint2 (&v)[5], float c0, float& s, float& q) {
  s = 0.f; q = 0.f;
#pragma unroll
  for (int i = 0; i < 5; i++) {
    float a = bf_lo(v[i].x) - c0, b = bf_hi(v[i].x) - c0, c = bf_lo(v[i].y) - c0, d = bf_hi(v[i].y) - c0;
    s += (a + b) + (c + d);
    q = fmaf(a, a, q); q = fmaf(b, b, q); q = fmaf(c, c, q); q = fmaf(d, d, q);
  }
}
__device__ __forceinline__ void ln_finish(const uint2 (&v)[5], float c0, float s, float q, uint2 (&o)[5]) {
  const float ms = s * (1.0f / 640.0f);
  const float mean = c0 + ms;
  q = fmaxf(fmaf(-ms, s, q), 0.f);
  const float mb = bfr(mean);
  const float vb = bfr(q * (1.0f / 640.0f));
  const float sd = bfr(sqrtf(bfr(vb + 1e-5f)));
  const float rs = 1.0f / sd;
  const uint32_t mbp = pack_bf16(mb, mb);
#pragma unroll
  for (int i = 0; i < 5; i++) {
    uint32_t a, b;
    asm("sub.rn.bf16x2 %0, %1, %2;" : "=r"(a) : "r"(v[i].x), "r"(mbp));
    asm("sub.rn.bf16x2 %0, %1, %2;" : "=r"(b) : "r"(v[i].y), "r"(mbp));
    o[i].x = pack_bf16(bf_lo(a) * rs, bf_hi(a) * rs);
    o[i].y = pack_bf16(bf_lo(b) * rs, bf_hi(b) * rs);
  }
}
__device__ __forceinline__ void ln_rows2(const uint2 (&v)[2][5], uint2 (&o)[2][5]) {
  const float c0 = __shfl_sync(0xffffffffu, bf_lo(v[0][0].x), 0), c1 = __shfl_sync(0xffffffffu, bf_lo(v[1][0].x), 0);
  float s0, q0, s1, q1;
  ln_stats_partial(v[0], c0, s0, q0);
  ln_stats_partial(v[1], c1, s1, q1);
#pragma unroll
  for (int o_ = 16; o_ > 0; o_ >>= 1) {
    s0 += __shfl_xor_sync(0xffffffffu, s0, o_); q0 += __shfl_xor_sync(0xffffffffu, q0, o_);
    s1 += __shfl_xor_sync(0xffffffffu, s1, o_); q1 += __shfl_xor_sync(0xffffffffu, q1, o_);
  }
  ln_finish(v[0], c0, s0, q0, o[0]);
  ln_finish(v[1], c1, s1, q1, o[1]);
}

__device__ __forceinline__ uint32_t silu_mul2(float ga, float gb, float ua, float ub) {
  const uint32_t gp = pack_bf16(ga, gb), up = pack_bf16(ua, ub);
  float g0 = bf_lo(gp), g1 = bf_hi(gp);
  float s0 = __fdividef(g0, 1.0f + __expf(-g0)), s1 = __fdividef(g1, 1.0f + __expf(-g1));
  uint32_t sp = pack_bf16(s0, s1);
  return pack_bf16(bf_lo(sp) * bf_lo(up), bf_hi(sp) * bf_hi(up));
}

__global__ void __launch_bounds__(NTHREADS, 1)
fused_kernel(const __grid_constant__ CUtensorMap tmZ, const __grid_constant__ CUtensorMap tmZst, const __grid_constant__ CUtensorMap tmWst, const __grid_constant__ CUtensorMap tmYst,
             const __grid_constant__ CUtensorMap tmYld, const __grid_constant__ CUtensorMap tmLN2, const __grid_constant__ CUtensorMap tmW1,
             const __grid_constant__ CUtensorMap tmW3, const __grid_constant__ CUtensorMap tmHH, const __grid_constant__ CUtensorMap tmW2ld,
             const __grid_constant__ CUtensorMap tmW2st, const __grid_constant__ CUtensorMap tmW2,
             const __nv_bfloat16* __restrict__ x, const __nv_bfloat16* __restrict__ w_r, const __nv_bfloat16* __restrict__ w_i,
             const __nv_bfloat16* __restrict__ w1, const __nv_bfloat16* __restrict__ w3, const __nv_bfloat16* __restrict__ w2,
             __nv_bfloat16* __restrict__ out, int dbg_stop) {
  extern __shared__ uint8_t smem_raw[];
  __shared__ __align__(16) Bars bars;
  const uint32_t sb = (smem_u32(smem_raw) + 1023u) & ~1023u;
  const int tid = threadIdx.x, warp = tid >> 5, lane = tid & 31, g = lane >> 2, q = lane & 3;
  const int cta = blockIdx.x;
  const int rb = cta >> 3, cb = cta & 7;
  const int wg = __shfl_sync(0xffffffffu, warp >> 2, 0);
  const int row0 = cta * 16 + (warp & 7) * 2;

  uint2 xv[2][5];
  if (warp < 8) {
#pragma unroll
    for (int r = 0; r < 2; r++)
#pragma unroll
      for (int i = 0; i < 5; i++) xv[r][i] = __ldg(reinterpret_cast<const uint2*>(x + (size_t)(row0 + r) * 640 + 128 * i + 4 * lane));
  } else {
#pragma unroll
    for (int r = 0; r < 2; r++)
#pragma unroll
      for (int i = 0; i < 5; i++) xv[r][i] = make_uint2(lane, tid);
    if (tid == 256) {
      PROFC(0); PROF(25);
      mbar_init(smem_u32(&bars.cst1), 1);
      asm volatile("fence.mbarrier_init.release.cluster;" ::: "memory");
      mbar_expect_tx(smem_u32(&bars.cst1), 10240);
      bulk_load(sb + SM_T1, c_T1, 10240, smem_u32(&bars.cst1));
      mbar_init(smem_u32(&bars.cst2), 1);
      mbar_init(smem_u32(&bars.xarr), 1);
      mbar_init(smem_u32(&bars.hs), 1);
      mbar_init(smem_u32(&bars.wrdy), 1);
      mbar_init(smem_u32(&bars.b1p), 1);
      mbar_init(smem_u32(&bars.p2d), (cta + 256 <= 320) ? 3 : 2);
      mbar_init(smem_u32(&bars.wraw), 1);
      for (int i = 0; i < 3; i++) mbar_init(smem_u32(&bars.T[i]), 1);
      mbar_init(smem_u32(&bars.Y), 1);
      mbar_init(smem_u32(&bars.Y2), 1);
      uint32_t tot = 0;
      for (int r = 0; r < 16; r++) {
        uint32_t st = (uint32_t)((cta >> 1) + 64 * (16 * (cta & 1) + r)) * 642u;
        tot += ((st + 642u + 15u) & ~15u) - (st & ~15u);
      }
      asm volatile("fence.mbarrier_init.release.cluster;" ::: "memory");
      mbar_expect_tx(smem_u32(&bars.wraw), 2 * tot);
      mbar_expect_tx(smem_u32(&bars.cst2), 8704 + 24576 + 16384);
    } else if (tid == 384) {
      for (int i = 0; i < 10; i++) { mbar_init(smem_u32(&bars.fullA[i]), 1); mbar_init(smem_u32(&bars.emptyA[i]), 1); }
      for (int i = 0; i < 4; i++) { mbar_init(smem_u32(&bars.fullB[i]), 1); mbar_init(smem_u32(&bars.emptyB[i]), 1); }
      for (int i = 0; i < 8; i++) { mbar_init(smem_u32(&bars.fullG[i]), 1); mbar_init(smem_u32(&bars.emptyG[i]), 1); }
      mbar_init(smem_u32(&bars.bfree), 1);
      for (int i = 0; i < 3; i++) mbar_init(smem_u32(&bars.f4l[i]), 1);
      asm volatile("fence.mbarrier_init.release.cluster;" ::: "memory");
    } else if (tid >= 288 && tid < 384 && cta == 0) {
      g_sync[(tid - 288 + 32) * 32] = 0;
      __threadfence();
    }
  }
  __syncthreads();

  if (wg < 2) {
    const uint32_t live = 1u;
    const uint32_t xs = sb + SM_XS + (warp & 7) * 3072;
    sts64p(xs + lane * 48 + 40, 0u, 0u, live);
    sts64p(xs + 1536 + lane * 48 + 40, 0u, 0u, live);
    uint32_t T[80];
    if (live) mbar_wait(smem_u32(&bars.cst1), 0);
    if (tid == 0) PROFC(16);
#pragma unroll
    for (int v = 0; v < 10; v++) {
      uint4 t = lds128(sb + SM_T1 + v * 512 + lane * 16);
      T[4*v] = t.x; T[4*v+1] = t.y; T[4*v+2] = t.z; T[4*v+3] = t.w;
    }
    {
      uint2 o[2][5];
      if (tid == 0 && (xv[0][4].x ^ xv[1][4].x ^ xv[0][4].y) != 0x9e3779b9u) mbar_arrive(smem_u32(&bars.xarr));
      else if (tid == 0) mbar_arrive(smem_u32(&bars.xarr));
      ln_rows2(xv, o);
#pragma unroll
      for (int r = 0; r < 2; r++)
#pragma unroll
        for (int i = 0; i < 5; i++) {
          int d = 128 * i + 4 * lane;
          int d1 = d / 20, d2 = d - d1 * 20;
          sts64p(xs + r * 1536 + d1 * 48 + d2 * 2, o[r][i].x, o[r][i].y, live);
        }
    }
    __syncwarp();
    if (tid == 0) PROFC(17);
#pragma unroll
    for (int v = 10; v < 20; v++) {
      uint4 t = lds128(sb + SM_T1 + v * 512 + lane * 16);
      T[4*v] = t.x; T[4*v+1] = t.y; T[4*v+2] = t.z; T[4*v+3] = t.w;
    }
    uint32_t PR[2][2][3], PI[2][2][3], sp[2][3];
#pragma unroll
    for (int r = 0; r < 2; r++)
#pragma unroll
      for (int nt = 0; nt < 3; nt++) {
        uint32_t b[4];
        ldsm4t(b, xs + r * 1536 + lane * 48 + nt * 16);
#pragma unroll
        for (int mt = 0; mt < 2; mt++) {
          float d[4] = {0.f, 0.f, 0.f, 0.f};
          mma16(d, T[(mt*2)*4], T[(mt*2)*4+1], T[(mt*2)*4+2], T[(mt*2)*4+3], b[0], b[1]);
          mma16(d, T[(mt*2+1)*4], T[(mt*2+1)*4+1], T[(mt*2+1)*4+2], T[(mt*2+1)*4+3], b[2], b[3]);
          const int tb = 16 + (mt * 3 + nt) * 4;
          float tc0 = __uint_as_float(T[tb]), ts0 = __uint_as_float(T[tb+1]), tc1 = __uint_as_float(T[tb+2]), ts1 = __uint_as_float(T[tb+3]);
          PR[r][mt][nt] = pack_bf16(d[0] * tc0 + d[2] * ts0, d[1] * tc1 + d[3] * ts1);
          PI[r][mt][nt] = pack_bf16(d[2] * tc0 - d[0] * ts0, d[3] * tc1 - d[1] * ts1);
        }
        sp[r][nt] = PI[r][0][nt];
        if (g == 0) PI[r][0][nt] = 0u;
      }
    const uint32_t zs = sb + SM_ZS + (warp & 1) * 8;
    const uint32_t zc = (uint32_t)((warp & 7) >> 1);
#define ZADDR(S_) (zs + (S_) * 64 + ((zc ^ (((S_) >> 1) & 3)) << 4))
#pragma unroll
    for (int t = 0; t < 5; t++) {
      float d0[4] = {0.f, 0.f, 0.f, 0.f}, d1[4] = {0.f, 0.f, 0.f, 0.f};
#pragma unroll
      for (int nt = 0; nt < 3; nt++) {
        const int bb = 40 + (nt * 5 + t) * 2;
        mma16(d0, PR[0][0][nt], PR[0][1][nt], PI[0][0][nt], PI[0][1][nt], T[bb], T[bb+1]);
        mma16(d1, PR[1][0][nt], PR[1][1][nt], PI[1][0][nt], PI[1][1][nt], T[bb], T[bb+1]);
      }
      const uint32_t s0 = g * 20 + 4 * t + q;
      sts64p(ZADDR(s0), pack_bf16(d0[0], d0[1]), pack_bf16(d1[0], d1[1]), live);
      sts64p(ZADDR(s0 + 160), pack_bf16(d0[2], d0[3]), pack_bf16(d1[2], d1[3]), live);
    }
#pragma unroll
    for (int t = 0; t < 3; t++) {
      float d[4] = {0.f, 0.f, 0.f, 0.f};
      const int bb = 70 + t * 3;
      mma16(d, sp[0][0], sp[1][0], sp[0][1], sp[1][1], T[bb], T[bb+1]);
      mma8(d, sp[0][2], sp[1][2], T[bb+2]);
      const uint32_t s0 = 320 + 4 * t + q;
      sts64p(ZADDR(s0), pack_bf16(d[0], d[1]), pack_bf16(d[2], d[3]), live && g == 0);
    }
    if (tid == 0) PROFC(18);
    fence_async_smem();
    named_bar(1, 256);
    if (warp == 0) {
      if (lane == 0) {
        PROFC(20);
        tma_store_2d(&tmZst, sb + SM_ZS, cta * 32, 0);
        tma_store_2d(&tmZst, sb + SM_ZS + 176 * 64, cta * 32, 176);
        bulk_commit();
        bulk_wait0();
        fence_async_global();
        PROFC(1);
      }
      __syncwarp();
      if (lane < 16) red_relaxed(&g_sync[(SY_B1 + lane) * 32]);
      if (lane == 0) { PROFC(2); PROF(26); }
    }
  } else if (wg == 2) {
    {
      const int t = tid - 256;
      if (warp == 8) {
        mbar_wait(smem_u32(&bars.xarr), 0);
        const uint32_t st = (uint32_t)((cta >> 1) + 64 * (16 * (cta & 1) + (lane & 15))) * 642u;
        const uint32_t a0 = st & ~15u, a1 = (st + 642u + 15u) & ~15u;
        const uint8_t* src = reinterpret_cast<const uint8_t*>((lane < 16) ? w_r : w_i) + a0;
        bulk_load(sb + SM_WS + lane * 672, src, a1 - a0, smem_u32(&bars.wraw));
      } else if (t == 32) {
        prefetch_tmap(&tmZst); prefetch_tmap(&tmWst); prefetch_tmap(&tmZ);
        mbar_wait(smem_u32(&bars.xarr), 0);
        bulk_load(sb + SM_FR, c_T2S, 24576, smem_u32(&bars.cst2));
        bulk_load(sb + SM_TW, c_T2W, 16384, smem_u32(&bars.cst2));
        bulk_load(sb + SM_T3, c_T3, 8704, smem_u32(&bars.cst2));
      } else if (t == 64) {
        prefetch_tmap(&tmYst); prefetch_tmap(&tmYld); prefetch_tmap(&tmLN2);
        prefetch_tmap(&tmW1); prefetch_tmap(&tmW3); prefetch_tmap(&tmHH); prefetch_tmap(&tmW2ld); prefetch_tmap(&tmW2st); prefetch_tmap(&tmW2);
      }
      __syncwarp();
      const int k1 = cta >> 1, h = cta & 1, qq = t & 3;
      uint32_t a[4];
#pragma unroll
      for (int jj = 0; jj < 4; jj++) {
        const int r = 4 * jj + qq;
        a[jj] = sb + SM_WS + r * 672 + (((uint32_t)(k1 + 64 * (16 * h + r)) * 642u) & 15u) + (t >> 2) * 2;
      }
      uint32_t dst = sb + SM_WST + (t >> 2) * 64 + qq * 16;
      mbar_wait(smem_u32(&bars.wraw), 0);
#pragma unroll 1
      for (int kd = t >> 2; kd <= 320; kd += 32) {
        uint32_t v[4];
#pragma unroll
        for (int jj = 0; jj < 4; jj++) {
          uint32_t re, im;
          asm volatile("ld.shared.u16 %0, [%1];" : "=r"(re) : "r"(a[jj]));
          asm volatile("ld.shared.u16 %0, [%1];" : "=r"(im) : "r"(a[jj] + 16 * 672));
          v[jj] = re | (im << 16);
          a[jj] += 64;
        }
        sts128(dst, v[0], v[1], v[2], v[3]);
        dst += 32 * 64;
      }
      fence_async_smem();
      named_bar(7, 128);
      if (warp == 8) {
        if (lane == 0) {
          tma_store_2d(&tmWst, sb + SM_WST, (k1 * 2 + h) * 32, 0);
          tma_store_2d(&tmWst, sb + SM_WST + 176 * 64, (k1 * 2 + h) * 32, 176);
          bulk_commit();
          bulk_wait0();
          fence_async_global();
        }
        __syncwarp();
        if (lane < 16) red_relaxed(&g_sync[(SY_W + lane) * 32]);
        if (lane == 0) {
          PROFC(19);
        }
      }
    }
  }
  if (dbg_stop == 1) return;

  {
    const int wtid = tid & 127, w = warp & 3;
    const uint32_t live = 1u;
    const int kd = cta + 128 * wg;
    if (warp == 14) {
      if (lane == 0) { wait_flag(&g_sync[(SY_W + (cta & 15)) * 32], NCTA); mbar_arrive(smem_u32(&bars.wrdy)); }
    } else if (warp == 15) {
      if (lane == 0) {
        wait_flag(&g_sync[(SY_B1 + (cta & 15)) * 32], NCTA);
        PROFC(3); PROF(27);
        fence_async_global();
        for (int j = 0; j < 3; j++) {
          const int kj = cta + 128 * j;
          if (kj <= 320) {
            int k1 = kj & 31, k2 = kj >> 5;
            if (k1 > 16) { k1 = 32 - k1; k2 = 19 - k2; }
            mbar_expect_tx(smem_u32(&bars.T[j]), 8192);
            tma_load_2d(sb + SM_TB + j * 16384, &tmZ, smem_u32(&bars.T[j]), 0, (k1 * 20 + k2) * 64);
          }
        }
        mbar_wait(smem_u32(&bars.T[0]), 0);
        mbar_wait(smem_u32(&bars.T[1]), 0);
        bulk_prefetch_l2(reinterpret_cast<const uint8_t*>(w2) + cta * 15360, 15360);
        bulk_prefetch_l2(reinterpret_cast<const uint8_t*>(w1) + cta * 15360, 15360);
        bulk_prefetch_l2(reinterpret_cast<const uint8_t*>(w3) + cta * 15360, 15360);
        mbar_arrive(smem_u32(&bars.b1p));
        mbar_wait(smem_u32(&bars.p2d), 0);
      }
      __syncwarp();
      if (lane < 16) red_relaxed(&g_sync[(SY_B2 + lane) * 32]);
      if (lane == 0) PROFC(5);
    } else if (wg < 3 && kd <= 320) {
      const uint32_t tb0 = sb + SM_TB + wg * 16384, tb1 = tb0 + 8192;
      mbar_wait(smem_u32(&bars.wrdy), 0);
      uint32_t wf[16];
#pragma unroll
      for (int i = 0; i < 2; i++)
#pragma unroll
        for (int h = 0; h < 2; h++) {
          uint4 t = __ldcg(reinterpret_cast<const uint4*>(g_Wt) + (((size_t)kd * 64 + 16 * w + g + 8 * i) * 2 + h) * 4 + q);
          wf[i*8 + h*4] = t.x; wf[i*8 + h*4 + 1] = t.y; wf[i*8 + h*4 + 2] = t.z; wf[i*8 + h*4 + 3] = t.w;
        }
      const int r20 = kd % 20, a20 = kd / 20;
      int slot; float scale = 1.0f / (2048.0f * 640.0f); float isg = 1.0f;
      if (r20 <= 10) { slot = 11 * a20 + r20; if ((r20 == 0 && a20 >= 1 && a20 <= 15) || r20 == 10) scale *= 2.0f; }
      else { slot = 11 * (31 - a20) + (20 - r20); isg = -1.0f; }
      const uint64_t dFR = mkdesc(sb + SM_FR, 16, 1024, 1), dFI = mkdesc(sb + SM_FI, 16, 1024, 1);
      const uint64_t dM2t = mkdesc(sb + SM_M2, 8192, 1024, 1);
      const uint64_t dM2k = mkdesc(sb + SM_M2, 16, 1024, 1);
      const uint64_t dT0 = mkdesc(tb0, 8192, 1024, 1), dT1 = mkdesc(tb1, 8192, 1024, 1);
      const uint32_t twa = sb + SM_TW + wtid * 16;
      const int mi = lane >> 3, rr = lane & 7;
      const uint32_t strow = (16 * w + (mi & 1) * 8 + rr) * 128;
      float Dm[32], Em[32];
      uint32_t af[16];
      mbar_wait(smem_u32(&bars.cst2), 0);
      mbar_wait(smem_u32(&bars.T[wg]), 0);
      if (tid == 0) PROFC(21);
#define STAG 0
      if (STAG && wg > 0) { const long long t0_ = clock64(); while (clock64() - t0_ < (long long)STAG * wg) { } }
      if (wtid == 0) TRC(56 + wg, 0);
      wg_fence();
#pragma unroll
      for (int k = 0; k < 4; k++) wgmma_ss_n64<0, 1>(Dm, dFR + k * 2, dT0 + k * 128, k);
#pragma unroll
      for (int k = 0; k < 4; k++) wgmma_ss_n64<0, 1>(Em, dFI + k * 2, dT0 + k * 128, k);
      wg_commit();
      wg_wait<0>();
      if (wtid == 0) TRC(56 + wg, 1);
#pragma unroll
      for (int jp = 0; jp < 4; jp++)
#pragma unroll
        for (int i = 0; i < 2; i++) {
          const uint4 t4 = lds128(twa + (i * 4 + jp) * 2048);
#pragma unroll
          for (int jj = 0; jj < 2; jj++) {
            const int j = 2 * jp + jj;
            float ur = Dm[4*j + 2*i] + Em[4*j + 2*i + 1], ui = Dm[4*j + 2*i + 1] - Em[4*j + 2*i];
            float tc = __uint_as_float(jj ? t4.z : t4.x), ts = __uint_as_float(jj ? t4.w : t4.y);
            af[jp * 4 + jj * 2 + i] = pack_bf16(ur * tc + ui * ts, ui * tc - ur * ts);
          }
        }
      if (wtid == 0) TRC(56 + wg, 2);
      wg_fence();
#pragma unroll
      for (int k = 0; k < 4; k++) wgmma_rs_n64<1>(Dm, af[4*k], af[4*k+1], af[4*k+2], af[4*k+3], dM2t + k * 128, k);
      wg_commit(); wg_wait<0>();
      if (wtid == 0) TRC(56 + wg, 3);
#pragma unroll
      for (int j = 0; j < 8; j++)
#pragma unroll
        for (int i = 0; i < 2; i++) {
          float xr = Dm[4*j + 2*i] * scale, xi = Dm[4*j + 2*i + 1] * scale;
          uint32_t ww = wf[i*8 + j];
          float wr = bf_lo(ww), wi = bf_hi(ww);
          af[(j >> 1) * 4 + (j & 1) * 2 + i] = pack_bf16(xr * wr - xi * wi, xr * wi + xi * wr);
        }
      if (wtid == 0) TRC(56 + wg, 4);
      wg_fence();
#pragma unroll
      for (int k = 0; k < 4; k++) wgmma_rs_n64<0>(Em, af[4*k], af[4*k+1], af[4*k+2], af[4*k+3], dM2k + k * 2, k);
      wg_commit(); wg_wait<0>();
      if (wtid == 0) TRC(56 + wg, 5);
#pragma unroll
      for (int jp = 0; jp < 4; jp++) {
        uint32_t o[4];
#pragma unroll
        for (int i = 0; i < 2; i++) {
          const uint4 t4 = lds128(twa + (i * 4 + jp) * 2048);
#pragma unroll
          for (int jj = 0; jj < 2; jj++) {
            const int j = 2 * jp + jj;
            float br = Em[4*j + 2*i], bi = Em[4*j + 2*i + 1];
            float tc = __uint_as_float(jj ? t4.z : t4.x), ts = __uint_as_float(jj ? t4.w : t4.y);
            o[jj*2 + i] = pack_bf16(br * tc - bi * ts, bi * tc + br * ts);
          }
        }
        stsm4p(tb1 + strow + (((2 * jp + (mi >> 1)) ^ rr) << 4), o[0], o[1], o[2], o[3], live);
      }
      if (wtid == 0) TRC(56 + wg, 6);
      fence_async_smem();
      named_bar(2 + wg, 128);
      wg_fence();
#pragma unroll
      for (int k = 0; k < 4; k++) wgmma_ss_n64<0, 1>(Dm, dFR + k * 2, dT1 + k * 128, k);
#pragma unroll
      for (int k = 0; k < 4; k++) wgmma_ss_n64<0, 1>(Em, dFI + k * 2, dT1 + k * 128, k);
      wg_commit(); wg_wait<0>();
#pragma unroll
      for (int jp = 0; jp < 4; jp++) {
        uint32_t o[4];
#pragma unroll
        for (int jj = 0; jj < 2; jj++)
#pragma unroll
          for (int i = 0; i < 2; i++) {
            const int j = 2 * jp + jj;
            float orr = Dm[4*j + 2*i] - Em[4*j + 2*i + 1], oi = Dm[4*j + 2*i + 1] + Em[4*j + 2*i];
            o[jj*2 + i] = pack_bf16(orr, oi * isg);
          }
        stsm4p(tb0 + strow + (((2 * jp + (mi >> 1)) ^ rr) << 4), o[0], o[1], o[2], o[3], live);
      }
      fence_async_smem();
      named_bar(2 + wg, 128);
      if (tid == 0) PROFC(22);
      if (wtid == 0) TRC(56 + wg, 7);
      if (wtid == 0) {
        tma_store_2d(&tmYst, tb0, 0, slot * 64);
        bulk_commit();
        bulk_wait0();
        fence_async_global();
        if (tid == 0) PROFC(4);
        mbar_arrive(smem_u32(&bars.p2d));
      }
    }
    if (warp == 12 || warp == 13) {
      const int kblk = cta >> 3, nblk = cta & 7;
      const uint32_t src = sb + 152576, dst = sb + 152576 + 5120;
      if (tid == 384) {
        mbar_wait(smem_u32(&bars.b1p), 0);
        for (int tt = 0; tt < 4; tt++) {
          uint32_t bar = smem_u32(&bars.fullB[tt]);
          mbar_expect_tx(bar, 16384);
          tma_load_2d(sb + SM_B + tt * 16384, &tmW1, bar, cb * 192, tt * 64);
          tma_load_2d(sb + SM_B + tt * 16384 + 8192, &tmW3, bar, cb * 192, tt * 64);
        }
      }
#pragma unroll 1
      for (int rd = 0; rd < 3; rd++) {
        if (tid == 384) {
          bulk_wait0();
          mbar_expect_tx(smem_u32(&bars.Y2), 5120);
          tma_load_2d(src, &tmW2ld, smem_u32(&bars.Y2), nblk * 80, kblk * 96 + rd * 32);
        }
        mbar_wait(smem_u32(&bars.Y2), rd & 1);
        named_bar(5, 64);
        for (int grp = warp - 12; grp < 10; grp += 2) {
          const int mi = lane >> 3, rr = lane & 7;
          uint32_t r4[4];
          ldsm4t(r4, src + (8 * (rr >> 1) + 2 * mi + (rr & 1)) * 160 + grp * 16);
          stsm4(dst + (grp * 8 + rr) * 64 + mi * 16, r4[0], r4[1], r4[2], r4[3]);
        }
        fence_async_smem();
        named_bar(5, 64);
        if (tid == 384) {
          tma_store_2d(&tmW2st, dst, kblk * 96 + rd * 32, nblk * 80);
          bulk_commit();
        }
      }
      if (warp == 12) {
        if (lane == 0) { bulk_wait0(); fence_async_global(); }
        __syncwarp();
        if (lane < 16) red_relaxed(&g_sync[(SY_W2T + lane) * 32]);
      }
    }
    if (dbg_stop == 2) return;
  }

  if (tid == 480) {
    wait_flag(&g_sync[(SY_B2 + (cta & 15)) * 32], NCTA);
    PROFC(6);
    fence_async_global();
    mbar_expect_tx(smem_u32(&bars.Y), 352 * 64 + 20480);
    tma_load_2d(sb + SM_YS, &tmYld, smem_u32(&bars.Y), cta * 32, 0);
    tma_load_2d(sb + SM_YS + 176 * 64, &tmYld, smem_u32(&bars.Y), cta * 32, 176);
    bulk_load(sb + SM_XR, x + (size_t)cta * 16 * 640, 20480, smem_u32(&bars.Y));
    if (cta == 0) { for (int i = 0; i < 32; i++) g_sync[i * 32] = 0; }
  }
  if (wg < 2) {
    const uint32_t live = 1u;
    const int wrp = warp & 7;
    uint32_t T[68];
    mbar_wait(smem_u32(&bars.cst2), 0);
#pragma unroll
    for (int v = 0; v < 17; v++) {
      uint4 t = lds128(sb + SM_T3 + v * 512 + lane * 16);
      T[4*v] = t.x; T[4*v+1] = t.y; T[4*v+2] = t.z; T[4*v+3] = t.w;
    }
    mbar_wait(smem_u32(&bars.Y), 0);
    if (tid == 0) PROFC(23);
    const uint32_t sel = (g & 1) ? 0x7632u : 0x5410u;
    const uint32_t yoff = (uint32_t)(wrp & 1) * 8;
    const uint32_t ychunk = (uint32_t)(wrp >> 1);
    uint32_t B[2][3][4];
    {
      const uint32_t sa = 22 * q + (g >> 1), sb_ = sa + 11;
      const uint32_t a0 = sb + SM_YS + sa * 64 + yoff, a1 = sb + SM_YS + sb_ * 64 + yoff;
      const uint32_t wa = (sa >> 1) & 3, wb = (sb_ >> 1) & 3;
      uint32_t ab[3], bb[3];
#pragma unroll
      for (int nt = 0; nt < 3; nt++) {
        ab[nt] = a0 + nt * 256 + ((ychunk ^ ((wa + 2 * nt) & 3)) << 4);
        bb[nt] = a1 + nt * 256 + ((ychunk ^ ((wb + 2 * nt) & 3)) << 4);
      }
#pragma unroll
      for (int nt = 0; nt < 3; nt++)
#pragma unroll
        for (int kh = 0; kh < 4; kh++) {
          uint2 a = lds64(ab[nt] + kh * 88 * 64);
          uint2 b = lds64(bb[nt] + kh * 88 * 64);
          B[0][nt][kh] = __byte_perm(a.x, b.x, sel);
          B[1][nt][kh] = __byte_perm(a.y, b.y, sel);
        }
    }
    const uint32_t yst = sb + SM_YST + wrp * 3200;
#pragma unroll
    for (int r = 0; r < 2; r++) {
      uint32_t UW[4][3];
#pragma unroll
      for (int mt = 0; mt < 2; mt++)
#pragma unroll
        for (int nt = 0; nt < 3; nt++) {
          float P[4] = {0.f, 0.f, 0.f, 0.f}, Q[4] = {0.f, 0.f, 0.f, 0.f};
#pragma unroll
          for (int kap = 0; kap < 2; kap++) {
            const int ca = (mt * 2 + kap) * 4, sa = 16 + ca;
            mma16(P, T[ca], T[ca+1], T[ca+2], T[ca+3], B[r][nt][2*kap], B[r][nt][2*kap+1]);
            mma16(Q, T[sa], T[sa+1], T[sa+2], T[sa+3], B[r][nt][2*kap], B[r][nt][2*kap+1]);
          }
#pragma unroll
          for (int hf = 0; hf < 2; hf++) {
            float vr = P[2*hf] - Q[2*hf+1], vi = P[2*hf+1] + Q[2*hf];
            const int tb = 32 + ((mt * 2 + hf) * 3 + nt) * 2;
            float tc = __uint_as_float(T[tb]), ts = __uint_as_float(T[tb+1]);
            UW[mt*2+hf][nt] = pack_bf16(vr * tc - vi * ts, vi * tc + vr * ts);
          }
        }
#pragma unroll
      for (int mt2 = 0; mt2 < 2; mt2++)
#pragma unroll
        for (int nu = 0; nu < 4; nu++) {
          float d[4] = {0.f, 0.f, 0.f, 0.f};
          const int ab = 56 + mt2 * 6;
          mma16(d, T[ab], T[ab+1], T[ab+2], T[ab+3], UW[nu][0], UW[nu][1]);
          mma8(d, T[ab+4], T[ab+5], UW[nu][2]);
          if (mt2 == 0) {
            sts32p(yst + r * 1600 + (g * 40 + 8 * nu + 2 * q) * 2, pack_bf16(d[0], d[1]), live);
            sts32p(yst + r * 1600 + ((g + 8) * 40 + 8 * nu + 2 * q) * 2, pack_bf16(d[2], d[3]), live);
          } else {
            sts32p(yst + r * 1600 + ((g + 16) * 40 + 8 * nu + 2 * q) * 2, pack_bf16(d[0], d[1]), live && g < 4);
          }
        }
    }
    __syncwarp();
    if (tid == 0) PROFC(24);
    {
      uint2 hv[2][5], o[2][5];
#pragma unroll
      for (int r = 0; r < 2; r++)
#pragma unroll
        for (int i = 0; i < 5; i++) {
          const int d = 128 * i + 4 * lane;
          uint2 y = lds64(yst + r * 1600 + ((d >> 5) * 40 + (d & 31)) * 2);
          uint2 xx = lds64(sb + SM_XR + (wrp * 2 + r) * 1280 + 256 * i + 8 * lane);
          asm("add.rn.bf16x2 %0, %1, %2;" : "=r"(hv[r][i].x) : "r"(xx.x), "r"(y.x));
          asm("add.rn.bf16x2 %0, %1, %2;" : "=r"(hv[r][i].y) : "r"(xx.y), "r"(y.y));
        }
      ln_rows2(hv, o);
#pragma unroll
      for (int r = 0; r < 2; r++)
#pragma unroll
        for (int i = 0; i < 5; i++) {
          sts64p(sb + SM_LS + (wrp * 2 + r) * 1280 + 256 * i + 8 * lane, o[r][i].x, o[r][i].y, live);
          sts64p(sb + SM_XR + (wrp * 2 + r) * 1280 + 256 * i + 8 * lane, hv[r][i].x, hv[r][i].y, live);
        }
    }
    if (live) {
      fence_async_smem();
      named_bar(1, 256);
      if (tid == 0) {
        bulk_store(g_ln2 + (size_t)cta * 16 * 640, sb + SM_LS, 20480);
        bulk_commit();
        bulk_wait0();
        fence_async_global();
        PROFC(7); red_relaxed(&g_sync[(SY_F3 + rb) * 32]); PROFC(8);
        bulk_store(g_h + (size_t)cta * 16 * 640, sb + SM_XR, 20480);
        bulk_commit();
        bulk_wait0();
        fence_async_global();
        mbar_arrive(smem_u32(&bars.hs));
      }
    }
  }
  if (dbg_stop == 3) return;

  if (warp >= 8) {
    asm volatile("setmaxnreg.dec.sync.aligned.u32 40;");
    if (warp == 8 && lane == 0) {
#pragma unroll 1
      for (int t = 4; t < 30; t++) {
        const int st = t & 3, c = t / 10, kb = t - c * 10;
        mbar_wait(smem_u32(&bars.emptyB[st]), ((t >> 2) - 1) & 1);
        TRC(t, 0);
        const uint32_t bar = smem_u32(&bars.fullB[st]);
        mbar_expect_tx(bar, 16384);
        tma_load_2d(sb + SM_B + st * 16384, &tmW1, bar, cb * 192 + c * 64, kb * 64);
        tma_load_2d(sb + SM_B + st * 16384 + 8192, &tmW3, bar, cb * 192 + c * 64, kb * 64);
      }
      for (int t = 30; t < 34; t++) mbar_wait(smem_u32(&bars.emptyB[t & 3]), ((t >> 2) - 1) & 1);
      mbar_arrive(smem_u32(&bars.bfree));
    } else if (warp == 9 && lane == 0) {
      wait_flag(&g_sync[(SY_W2T + (cta & 15)) * 32], NCTA);
      wait_flag(&g_sync[(SY_F3 + rb) * 32], 8);
      PROFC(9);
      fence_async_global();
#pragma unroll 1
      for (int kb = 0; kb < 10; kb++) {
        const uint32_t bar = smem_u32(&bars.fullA[kb]);
        if (kb == 8) mbar_wait(smem_u32(&bars.hs), 0);
        mbar_expect_tx(bar, 16384);
        TRC(kb, 2);
        tma_load_2d(sb + SM_A + kb * 16384, &tmLN2, bar, kb * 64, rb * 128);
      }
#pragma unroll 1
      for (int i = 0; i < 24; i++) {
        const int st = i & 7;
        if (st == 0) { mbar_wait(smem_u32(&bars.f4l[i >> 3]), 0); fence_async_global(); }
        if (i < 8) {
          const int lastA = (i * 26624 + 26623) >> 14;
          if (lastA <= 9) mbar_wait(smem_u32(&bars.emptyA[lastA]), 0);
          else { mbar_wait(smem_u32(&bars.emptyA[9]), 0); mbar_wait(smem_u32(&bars.bfree), 0); }
        } else {
          mbar_wait(smem_u32(&bars.emptyG[st]), ((i >> 3) - 1) & 1);
        }
        TRC(30 + i, 2);
        const uint32_t bar = smem_u32(&bars.fullG[st]);
        mbar_expect_tx(bar, 26624);
        const int k0 = 192 * st + 64 * (i >> 3);
        tma_load_2d(sb + st * 26624, &tmHH, bar, k0, rb * 128);
        tma_load_2d(sb + st * 26624 + 16384, &tmW2, bar, k0, cb * 80);
      }
    } else if (warp == 15 && lane == 0) {
      for (int c = 0; c < 3; c++) { wait_flag(&g_sync[(SY_F4 + c * 16 + rb) * 32], 8); mbar_arrive(smem_u32(&bars.f4l[c])); }
    } else if (warp == 10) {
#pragma unroll 1
      for (int c = 0; c < 3; c++) {
        named_bar(6 + (c & 1), 160);
        if (lane == 0) red_release(&g_sync[(SY_F4 + c * 16 + rb) * 32]);
      }
    }
  } else {
    asm volatile("setmaxnreg.inc.sync.aligned.u32 208;");
    const int w = warp & 3;
    const bool elect = (tid & 127) == 0;
    const int rowl = w * 16 + g;
    const uint64_t dA0 = mkdesc(sb + SM_A, 16, 1024, 1);
    const uint64_t dB0 = mkdesc(sb + SM_B, 8192, 1024, 1);
    const uint32_t bFullA = smem_u32(&bars.fullA[0]), bEmptyA = smem_u32(&bars.emptyA[0]);
    const uint32_t bFullB = smem_u32(&bars.fullB[0]), bEmptyB = smem_u32(&bars.emptyB[0]);
#pragma unroll 1
    for (int c = (wg == 1) ? -1 : 0; c < 3; c += 2) {
      float acc0[64], acc1[64];
#pragma unroll
      for (int z = 0; z < 64; z++) { acc0[z] = 0.f; acc1[z] = 0.f; }
      if (c >= 0) {
      if (elect) TRC(60 + c, 0);
      if (c > 0) named_bar(4 + (c & 1), 256);
      if (elect) TRC(60 + c, 1);
      if (c == 0) mbar_wait(bFullA, 0);
      mbar_wait(bFullB + ((c * 10) & 3) * 8, ((c * 10) >> 2) & 1);
      wg_fence();
#pragma unroll 1
      for (int kb = 0; kb < 10; kb++) {
        const int t = c * 10 + kb;
        const uint64_t da = dA0 + kb * 1024, db = dB0 + (t & 3) * 1024;
        const int kn = (kb < 9) ? kb + 1 : kb, tn = c * 10 + kn;
        wg_fence();
#pragma unroll
        for (int k = 0; k < 4; k++) wgmma_ss_n128<0, 1>(acc0, da + k * 2, db + k * 128, 1);
        wg_commit();
        wg_wait<1>();
        mbar_arrive_if(bEmptyB + ((t - 1) & 3) * 8, elect && kb > 0);
        mbar_arrive_if(bEmptyA + ((kb > 0) ? kb - 1 : 0) * 8, elect && kb > 0 && c == 2);
        uint32_t ok = mbar_test(bFullB + (tn & 3) * 8, (tn >> 2) & 1) & mbar_test(bFullA + kn * 8, 0);
#pragma unroll
        for (int k = 0; k < 4; k++) wgmma_ss_n128<0, 1>(acc1, da + 512 + k * 2, db + k * 128, 1);
        wg_commit();
        if (!ok) { mbar_wait(bFullA + kn * 8, 0); mbar_wait(bFullB + (tn & 3) * 8, (tn >> 2) & 1); }
      }
      asm volatile("bar.arrive %0, 256;" ::"r"(4 + ((c + 1) & 1)) : "memory");
      wg_wait<0>();
      if (elect) { mbar_arrive(bEmptyB + ((c * 10 + 9) & 3) * 8); if (c == 2) mbar_arrive(bEmptyA + 9 * 8); }
      if (tid == 0 || tid == 128) PROFC(10 + c);
      if (elect) TRC(60 + c, 2);
      }
      uint4* hp = reinterpret_cast<uint4*>(g_hh + (size_t)(rb * 128 + rowl) * 1536 + cb * 192 + (c & 3) * 64 + 8 * q);
#pragma unroll 1
      for (int mt = 0; mt < 2; mt++) {
#pragma unroll
        for (int G = 0; G < 2; G++) {
          uint32_t v[2][4];
#pragma unroll
          for (int jj = 0; jj < 4; jj++) {
            const int j = 4 * G + jj;
            v[0][jj] = silu_mul2(acc0[4*j], acc0[4*j+1], acc0[32+4*j], acc0[32+4*j+1]);
            v[1][jj] = silu_mul2(acc0[4*j+2], acc0[4*j+3], acc0[32+4*j+2], acc0[32+4*j+3]);
          }
          stg128p(hp + 4 * G, v[0][0], v[0][1], v[0][2], v[0][3], c >= 0);
          stg128p(hp + 8 * 192 + 4 * G, v[1][0], v[1][1], v[1][2], v[1][3], c >= 0);
        }
        hp += 64 * 192;
#pragma unroll
        for (int z = 0; z < 64; z++) acc0[z] = acc1[z];
      }
      if (c >= 0) {
      if (elect) TRC(60 + c, 3);
      asm volatile("bar.arrive %0, 160;" ::"r"(6 + (c & 1)) : "memory");
      }
    }
    uint4 hr[5];
    mbar_wait(smem_u32(&bars.fullG[0]), 0);
#pragma unroll
    for (int i = 0; i < 5; i++) {
      const int idx = tid + 256 * i, r = idx / 10, cc = idx - r * 10;
      hr[i] = __ldcg(reinterpret_cast<const uint4*>(g_h + (size_t)(rb * 128 + r) * 640 + cb * 80 + cc * 8));
    }
    if (wg == 1) {
      float acc0[40], acc1[40];
#pragma unroll
      for (int z = 0; z < 40; z++) { acc0[z] = 0.f; acc1[z] = 0.f; }
      const uint64_t dG0 = mkdesc(sb, 16, 1024, 1);
      const uint32_t bFullG = smem_u32(&bars.fullG[0]), bEmptyG = smem_u32(&bars.emptyG[0]);
      named_bar(5, 256);
      mbar_wait(bFullG, 0); mbar_wait(bFullG + 8, 0);
#pragma unroll 1
      for (int i = 0; i < 24; i += 2) {
        const int st = i & 7;
        const uint64_t da = dG0 + st * 1664, dw = da + 1024;
        const int in = (i < 22) ? i + 2 : i;
        wg_fence();
#pragma unroll
        for (int k = 0; k < 8; k++) wgmma_ss_n80<0, 0>(acc0, da + (k >> 2) * 1664 + (k & 3) * 2, dw + (k >> 2) * 1664 + (k & 3) * 2, 1);
        wg_commit();
        wg_wait<1>();
        mbar_arrive_if(bEmptyG + ((st + 6) & 7) * 8, elect && i > 0);
        mbar_arrive_if(bEmptyG + ((st + 7) & 7) * 8, elect && i > 0);
        const int pn = (in >> 3) & 1;
        uint32_t ok = mbar_test(bFullG + (in & 7) * 8, pn) & mbar_test(bFullG + (in & 7) * 8 + 8, pn);
#pragma unroll
        for (int k = 0; k < 8; k++) wgmma_ss_n80<0, 0>(acc1, da + 512 + (k >> 2) * 1664 + (k & 3) * 2, dw + (k >> 2) * 1664 + (k & 3) * 2, 1);
        wg_commit();
        if (!ok) { mbar_wait(bFullG + (in & 7) * 8, pn); mbar_wait(bFullG + (in & 7) * 8 + 8, pn); }
      }
      wg_wait<0>();
      if (tid == 128) PROFC(13);
      const int mi = lane >> 3, rr = lane & 7;
      const uint32_t os = sb + SM_OS + (w * 16 + (mi & 1) * 8 + rr) * 176 + (mi >> 1) * 16;
#pragma unroll
      for (int jp = 0; jp < 5; jp++) {
        stsm4(os + jp * 32, pack_bf16(acc0[8*jp], acc0[8*jp+1]), pack_bf16(acc0[8*jp+2], acc0[8*jp+3]),
              pack_bf16(acc0[8*jp+4], acc0[8*jp+5]), pack_bf16(acc0[8*jp+6], acc0[8*jp+7]));
        stsm4(os + 64 * 176 + jp * 32, pack_bf16(acc1[8*jp], acc1[8*jp+1]), pack_bf16(acc1[8*jp+2], acc1[8*jp+3]),
              pack_bf16(acc1[8*jp+4], acc1[8*jp+5]), pack_bf16(acc1[8*jp+6], acc1[8*jp+7]));
      }
    }
    if (tid == 128) PROFC(29);
    if (tid == 0) PROFC(30);
    named_bar(4, 256);
    if (tid == 128) PROFC(31);
#pragma unroll
    for (int i = 0; i < 5; i++) {
      const int idx = tid + 256 * i, r = idx / 10, cc = idx - r * 10;
      const uint4 m = lds128(sb + SM_OS + r * 176 + cc * 16);
      uint4 o;
      asm("add.rn.bf16x2 %0, %1, %2;" : "=r"(o.x) : "r"(hr[i].x), "r"(m.x));
      asm("add.rn.bf16x2 %0, %1, %2;" : "=r"(o.y) : "r"(hr[i].y), "r"(m.y));
      asm("add.rn.bf16x2 %0, %1, %2;" : "=r"(o.z) : "r"(hr[i].z), "r"(m.z));
      asm("add.rn.bf16x2 %0, %1, %2;" : "=r"(o.w) : "r"(hr[i].w), "r"(m.w));
      stg128(out + (size_t)(rb * 128 + r) * 640 + cb * 80 + cc * 8, o.x, o.y, o.z, o.w);
    }
    if (tid == 128) { PROFC(14); PROF(28); }
  }
}

typedef CUresult (*EncodeFn)(CUtensorMap*, CUtensorMapDataType, cuuint32_t, void*, const cuuint64_t*, const cuuint64_t*,
                             const cuuint32_t*, const cuuint32_t*, CUtensorMapInterleave, CUtensorMapSwizzle,
                             CUtensorMapL2promotion, CUtensorMapFloatOOBfill);

static CUtensorMap make_map(EncodeFn enc, const void* ptr, int rank, const cuuint64_t* dims, const cuuint64_t* strides,
                            const cuuint32_t* box, CUtensorMapSwizzle sw) {
  CUtensorMap m;
  cuuint32_t es[5] = {1, 1, 1, 1, 1};
  enc(&m, CU_TENSOR_MAP_DATA_TYPE_BFLOAT16, (cuuint32_t)rank, const_cast<void*>(ptr), dims, strides, box, es,
      CU_TENSOR_MAP_INTERLEAVE_NONE, sw, CU_TENSOR_MAP_L2_PROMOTION_L2_256B, CU_TENSOR_MAP_FLOAT_OOB_FILL_NONE);
  return m;
}

static int g_dbg_stop = 0;

extern "C" void kernel_launch(void* const* d_in, const int* in_sizes, int n_in, void* d_out, int out_size) {
  (void)in_sizes; (void)n_in; (void)out_size;
  const __nv_bfloat16* x = (const __nv_bfloat16*)d_in[0];
  const __nv_bfloat16* w_r = (const __nv_bfloat16*)d_in[1];
  const __nv_bfloat16* w_i = (const __nv_bfloat16*)d_in[2];
  const __nv_bfloat16* w1 = (const __nv_bfloat16*)d_in[4];
  const __nv_bfloat16* w3 = (const __nv_bfloat16*)d_in[5];
  const __nv_bfloat16* w2 = (const __nv_bfloat16*)d_in[6];

  static EncodeFn enc = nullptr;
  static void *pZ, *pY, *pLN2, *pHH, *pW2t, *pWt;
  if (!enc) {
    void* fn = nullptr;
    cudaDriverEntryPointQueryResult qr;
    cudaGetDriverEntryPoint("cuTensorMapEncodeTiled", &fn, cudaEnableDefault, &qr);
    enc = (EncodeFn)fn;
    cudaGetSymbolAddress(&pZ, g_Z);
    cudaGetSymbolAddress(&pY, g_Y);
    cudaGetSymbolAddress(&pLN2, g_ln2);
    cudaGetSymbolAddress(&pHH, g_hh);
    cudaGetSymbolAddress(&pW2t, g_w2t);
    cudaGetSymbolAddress(&pWt, g_Wt);
    cudaFuncSetAttribute(fused_kernel, cudaFuncAttributeMaxDynamicSharedMemorySize, SM_TOTAL + 1024);
  }
  CUtensorMap tmZ, tmZst, tmWst, tmYst, tmYld, tmLN2, tmW1, tmW3, tmHH, tmW2ld, tmW2st, tmW2;
  { cuuint64_t d[2] = {64, 340 * 64}, s[1] = {128}; cuuint32_t b[2] = {64, 64}; tmZ = make_map(enc, pZ, 2, d, s, b, CU_TENSOR_MAP_SWIZZLE_128B); }
  { cuuint64_t d[2] = {4096, 340}, s[1] = {8192}; cuuint32_t b[2] = {32, 176}; tmZst = make_map(enc, pZ, 2, d, s, b, CU_TENSOR_MAP_SWIZZLE_64B); }
  { cuuint64_t d[2] = {4096, 321}, s[1] = {8192}; cuuint32_t b[2] = {32, 176}; tmWst = make_map(enc, pWt, 2, d, s, b, CU_TENSOR_MAP_SWIZZLE_NONE); }
  { cuuint64_t d[2] = {64, 352 * 64}, s[1] = {128}; cuuint32_t b[2] = {64, 64}; tmYst = make_map(enc, pY, 2, d, s, b, CU_TENSOR_MAP_SWIZZLE_128B); }
  { cuuint64_t d[2] = {4096, 352}, s[1] = {8192}; cuuint32_t b[2] = {32, 176}; tmYld = make_map(enc, pY, 2, d, s, b, CU_TENSOR_MAP_SWIZZLE_64B); }
  { cuuint64_t d[2] = {640, 2048}, s[1] = {1280}; cuuint32_t b[2] = {64, 128}; tmLN2 = make_map(enc, pLN2, 2, d, s, b, CU_TENSOR_MAP_SWIZZLE_128B); }
  { cuuint64_t d[2] = {1536, 640}, s[1] = {3072}; cuuint32_t b[2] = {64, 64}; tmW1 = make_map(enc, w1, 2, d, s, b, CU_TENSOR_MAP_SWIZZLE_128B);
    tmW3 = make_map(enc, w3, 2, d, s, b, CU_TENSOR_MAP_SWIZZLE_128B); }
  { cuuint64_t d[2] = {1536, 2048}, s[1] = {3072}; cuuint32_t b[2] = {64, 128}; tmHH = make_map(enc, pHH, 2, d, s, b, CU_TENSOR_MAP_SWIZZLE_128B); }
  { cuuint64_t d[2] = {640, 1536}, s[1] = {1280}; cuuint32_t b[2] = {80, 32}; tmW2ld = make_map(enc, w2, 2, d, s, b, CU_TENSOR_MAP_SWIZZLE_NONE); }
  { cuuint64_t d[2] = {1536, 640}, s[1] = {3072}; cuuint32_t b[2] = {32, 80}; tmW2st = make_map(enc, pW2t, 2, d, s, b, CU_TENSOR_MAP_SWIZZLE_NONE);
    cuuint32_t b2[2] = {64, 80}; tmW2 = make_map(enc, pW2t, 2, d, s, b2, CU_TENSOR_MAP_SWIZZLE_128B); }
  fused_kernel<<<NCTA, NTHREADS, SM_TOTAL + 1024, cudaStreamPerThread>>>(tmZ, tmZst, tmWst, tmYst, tmYld, tmLN2, tmW1, tmW3, tmHH, tmW2ld, tmW2st, tmW2, x, w_r, w_i, w1, w3, w2,
                                                     (__nv_bfloat16*)d_out, g_dbg_stop);
}
```
